```python
import torch

def _softmax(x, axis=-1):
    return torch.softmax(x, dim=axis)
def _gelu(x):
    return torch.nn.functional.gelu(x, approximate="tanh")
def _silu(x):
    return torch.nn.functional.silu(x)
def _sigmoid(x):
    return torch.sigmoid(x)
def _layernorm(x, axis=-1, eps=1e-5):
    m = x.mean(dim=axis, keepdim=True)
    v = x.var(dim=axis, keepdim=True, unbiased=False)
    return (x - m) / torch.sqrt(v + eps)
def _scatter_add(tgt, idx, src, axis=0):
    return tgt.clone().index_add_(axis, idx, src)
def _segment_sum(src, seg, n):
    out = torch.zeros((n,) + src.shape[1:], dtype=src.dtype)
    return out.index_add_(0, seg, src)
def _pad(x, pw):
    flat = tuple(v for pair in reversed(pw) for v in pair)
    return torch.nn.functional.pad(x, flat)

kernel_name = 'sequential_preLN__mha_block_cached__glu_gated_geglu__decode'

def setup_inputs():

    _w = (lambda a: (lambda t: t.to(torch.bfloat16) if t.is_floating_point() else t)(torch.as_tensor(a)))
    def _A_setup():
        B, Sq, D = 1, 1, 576
        H, Sk, Dh = 32, 16384, 128
        return {
            "x": _w((lambda *s: torch.randn(*s, dtype=torch.bfloat16) * 0.05)(B, Sq, D)),
            "k_cache": _w((lambda *s: torch.randn(*s, dtype=torch.bfloat16) * 3.2)(B, H, Sk, Dh)),
            "v_cache": _w((lambda *s: torch.randn(*s, dtype=torch.bfloat16) * 1.6)(B, H, Sk, Dh)),
            "wq": _w((lambda *s: torch.randn(*s, dtype=torch.bfloat16) * 3.2)(D, H * Dh) * (D ** -0.5)),
            "wo": _w((lambda *s: torch.randn(*s, dtype=torch.bfloat16) * 1.6)(H * Dh, D) * ((H * Dh) ** -0.5)),
        }
    _A_in = _A_setup()

    def _B_setup():
        B, S, Dm, Df = 1, 1, 576, 4608
        return {
            "x": _w((lambda *s: torch.randn(*s, dtype=torch.bfloat16) * 0.05)(B, S, Dm)),
            "w_gate": _w((lambda *s: torch.randn(*s, dtype=torch.bfloat16) * 1.6)(Dm, Df) * (Dm ** -0.5)),
            "w_up": _w((lambda *s: torch.randn(*s, dtype=torch.bfloat16) * 1.6)(Dm, Df) * (Dm ** -0.5)),
            "w_down": _w((lambda *s: torch.randn(*s, dtype=torch.bfloat16) * 1.6)(Df, Dm) * (Df ** -0.5)),
        }
    _B_in = _B_setup()

    return {
        "A_x": _A_in["x"],
        "A_k_cache": _A_in["k_cache"],
        "A_v_cache": _A_in["v_cache"],
        "A_wq": _A_in["wq"],
        "A_wo": _A_in["wo"],
        "B_x": _B_in["x"],
        "B_w_gate": _B_in["w_gate"],
        "B_w_up": _B_in["w_up"],
        "B_w_down": _B_in["w_down"],
    }

def reference(A_x, A_k_cache, A_v_cache, A_wq, A_wo, B_x, B_w_gate, B_w_up, B_w_down):
    def _A_ref(x, k_cache, v_cache, wq, wo):
        B, Sq, D = x.shape
        H, Dh = 32, 128
        q = (lambda x, *d: x.permute(*d))((x @ wq).reshape(B, Sq, H, Dh), 0, 2, 1, 3)
        scores = torch.einsum("bhqd,bhkd->bhqk", q, k_cache) * (Dh ** -0.5)
        p = _softmax(scores, axis=-1)
        o = torch.einsum("bhqk,bhkd->bhqd", p, v_cache)
        return (lambda x, *d: x.permute(*d))(o, 0, 2, 1, 3).reshape(B, Sq, H * Dh) @ wo

    def _B_ref(x, w_gate, w_up, w_down):
        g = torch.einsum("bsd,df->bsf", x, w_gate)
        u = torch.einsum("bsd,df->bsf", x, w_up)
        h = _gelu(g) * u
        return torch.einsum("bsf,fd->bsd", h, w_down)

    x = A_x
    h = x + _A_ref(_layernorm(x, axis=-1), A_k_cache, A_v_cache, A_wq, A_wo)
    h2 = h + _B_ref(_layernorm(h, axis=-1), B_w_gate, B_w_up, B_w_down)
    return h2
```

```cpp
#include <cuda_runtime.h>
#include <cuda_bf16.h>
#include <cuda.h>
#include <stdint.h>

namespace {

constexpr int DM = 576;
constexpr int NH = 32;
constexpr int SK = 16384;
constexpr int DH = 128;
constexpr int DFF = 4608;

constexpr int NCTA = 128;
constexpr int TK = 32;
constexpr int TILE_B = TK * DH * 2;
constexpr int SLOT_B = 2 * TILE_B;
constexpr int NTILES = NH * (SK / TK);
#define LA_ 4
constexpr int LA = LA_;
constexpr int S = 12;
#define DCAP_ 4
constexpr int DCAP = DCAP_;
#define DCAPW_ 2
constexpr int DCAPW = DCAPW_;
#define WK1 0
#define WD1 1
#define DRYRUN 0
#define NSX_ 2
constexpr int NS = DCAP + NSX_ * LA;
#define NW_ 8
constexpr int NW = NW_;
constexpr int PS = 16;
constexpr int NTAIL = 288;
constexpr int NTHREADS = DRYRUN ? 352 : 320;
constexpr int NWP = 12;
constexpr int FC = DFF / NCTA;
constexpr int FCP = 40;
constexpr int WP = DM * 2 + 16;
constexpr int NOWN = 72;
constexpr int GC = 32;
constexpr int NGC = NCTA / GC;
constexpr int PREC = 132;

static_assert(S >= NW + DCAP, "parity aliasing");
static_assert(NWP <= S && DCAPW <= DCAP && PS >= NW, "ring");

constexpr int SM_Q = S * SLOT_B;
constexpr int SM_PR = SM_Q + NH * DH * 2;
constexpr int SM_GP = SM_PR + PS * PREC * 4;
constexpr int SM_RED = SM_GP + NGC * 36 * 4;
constexpr int SM_H = SM_RED + 16 * 72 * 4;
constexpr int SM_HN = SM_H + DM * 4;
constexpr int SM_SMALL = SM_HN + DM * 4;
constexpr int SM_BAR = SM_SMALL + 9 * 32 * 4 + 64 * 4;
constexpr int SM_TOTAL = SM_BAR + (2 * S + 2 * PS + NH) * 8;
static_assert(SM_TOTAL <= 232448, "smem");

__device__ unsigned int g_epoch;
__device__ unsigned int g_ctr[2][32];
__device__ __align__(16) unsigned long long g_q[NH * DH];
__device__ __align__(16) unsigned long long g_part[NH * NCTA * PREC];
__device__ __align__(16) unsigned long long g_y[NOWN * NCTA * 8];
__device__ __align__(16) unsigned long long g_h[DM];
__device__ __align__(16) unsigned long long g_z[NOWN * NCTA * 8];
#define STAMP(i)
#define STAMPD(i, dep)
#define PSTAMP(i)

constexpr unsigned SPIN_LIMIT = 1u << 22;
#define SPIN_FAIL() __trap()

__device__ __forceinline__ uint32_t smem_u32(const void* p) { return (uint32_t)__cvta_generic_to_shared(p); }
__device__ __forceinline__ void mbar_init(uint32_t bar, uint32_t cnt) {
    asm volatile("mbarrier.init.shared::cta.b64 [%0], %1;" ::"r"(bar), "r"(cnt) : "memory");
}
__device__ __forceinline__ void mbar_expect_tx(uint32_t bar, uint32_t bytes) {
    asm volatile("mbarrier.arrive.expect_tx.shared::cta.b64 _, [%0], %1;" ::"r"(bar), "r"(bytes) : "memory");
}
__device__ __forceinline__ void mbar_arrive(uint32_t bar) {
    asm volatile("mbarrier.arrive.shared::cta.b64 _, [%0];" ::"r"(bar) : "memory");
}
__device__ __forceinline__ bool mbar_try(uint32_t bar, uint32_t parity) {
    uint32_t ok;
    asm volatile("{\n.reg .pred p;\nmbarrier.try_wait.parity.shared::cta.b64 p, [%1], %2;\nselp.u32 %0, 1, 0, p;\n}\n"
                 : "=r"(ok) : "r"(bar), "r"(parity) : "memory");
    return ok != 0;
}
__device__ __forceinline__ bool mbar_test(uint32_t bar, uint32_t parity) {
    uint32_t ok;
    asm volatile("{\n.reg .pred p;\nmbarrier.test_wait.parity.shared::cta.b64 p, [%1], %2;\nselp.u32 %0, 1, 0, p;\n}\n"
                 : "=r"(ok) : "r"(bar), "r"(parity) : "memory");
    return ok != 0;
}
__device__ __forceinline__ void mbar_wait(uint32_t bar, uint32_t parity) {
    unsigned n = 0; bool return_from_spin = false;
    while (!mbar_try(bar, parity)) {
        if (++n > SPIN_LIMIT) SPIN_FAIL();
        if (return_from_spin) break;
    }
}
__device__ __forceinline__ void bulk_load(uint32_t dst, const void* src, uint32_t bytes, uint32_t bar, uint64_t pol) {
    asm volatile("cp.async.bulk.shared::cluster.global.mbarrier::complete_tx::bytes.L2::cache_hint [%0], [%1], %2, [%3], %4;"
                 ::"r"(dst), "l"(src), "r"(bytes), "r"(bar), "l"(pol) : "memory");
}
__device__ __forceinline__ void tma_load_2d(uint32_t dst, const CUtensorMap* map, int c0, int c1, uint32_t bar) {
    asm volatile("cp.async.bulk.tensor.2d.shared::cluster.global.mbarrier::complete_tx::bytes [%0], [%1, {%3, %4}], [%2];"
                 ::"r"(dst), "l"(map), "r"(bar), "r"(c0), "r"(c1) : "memory");
}
__device__ __forceinline__ void bar_tail() { asm volatile("bar.sync 1, 288;" ::: "memory"); }

__device__ __forceinline__ uint4 lds128(uint32_t a) {
    uint4 v; asm volatile("ld.shared.v4.u32 {%0,%1,%2,%3}, [%4];" : "=r"(v.x), "=r"(v.y), "=r"(v.z), "=r"(v.w) : "r"(a)); return v;
}
__device__ __forceinline__ uint2 lds64(uint32_t a) {
    uint2 v; asm volatile("ld.shared.v2.u32 {%0,%1}, [%2];" : "=r"(v.x), "=r"(v.y) : "r"(a)); return v;
}
__device__ __forceinline__ uint32_t lds32(uint32_t a) {
    uint32_t v; asm volatile("ld.shared.u32 %0, [%1];" : "=r"(v) : "r"(a)); return v;
}
__device__ __forceinline__ float bflo(uint32_t w) { return __uint_as_float(w << 16); }
__device__ __forceinline__ float bfhi(uint32_t w) { return __uint_as_float(w & 0xffff0000u); }
__device__ __forceinline__ float bfr(float x) { return __bfloat162float(__float2bfloat16_rn(x)); }

__device__ __forceinline__ unsigned long long pk(float v, unsigned tag) {
    return ((unsigned long long)tag << 32) | (unsigned long long)__float_as_uint(v);
}
__device__ __forceinline__ float pkv(unsigned long long a) { return __uint_as_float((unsigned)a); }
__device__ __forceinline__ bool pkok(unsigned long long a, unsigned tag) { return (unsigned)(a >> 32) == tag; }
__device__ __forceinline__ void st_pk2(unsigned long long* p, float v0, float v1, unsigned tag) {
    asm volatile("st.relaxed.gpu.global.v2.b64 [%0], {%1, %2};" ::"l"(p), "l"(pk(v0, tag)), "l"(pk(v1, tag)) : "memory");
}
__device__ __forceinline__ void ld_raw2(const unsigned long long* p, unsigned long long& a, unsigned long long& b) {
    asm volatile("ld.relaxed.gpu.global.v2.b64 {%0, %1}, [%2];" : "=l"(a), "=l"(b) : "l"(p) : "memory");
}

__device__ __forceinline__ void bar_tail_p(unsigned p) {
    asm volatile("{\n.reg .pred q;\nsetp.ne.u32 q, %0, 0;\n@q bar.sync 1, 288;\n}" ::"r"(p) : "memory");
}
__device__ __forceinline__ void mbar_wait_p(uint32_t bar, uint32_t parity, unsigned p) {
    unsigned n = 0, ok; bool return_from_spin = false;
    do {
        asm volatile("{\n.reg .pred q, r;\nsetp.ne.u32 q, %3, 0;\nsetp.eq.u32 r, %3, 0;\n"
                     "@q mbarrier.try_wait.parity.shared::cta.b64 r, [%1], %2;\nselp.u32 %0, 1, 0, r;\n}"
                     : "=r"(ok) : "r"(bar), "r"(parity), "r"(p) : "memory");
        if (++n > SPIN_LIMIT) SPIN_FAIL();
        if (return_from_spin) break;
    } while (!ok);
}
__device__ __forceinline__ void st_pk1_p(unsigned long long* a, float v, unsigned tag, unsigned p) {
    asm volatile("{\n.reg .pred q;\nsetp.ne.u32 q, %2, 0;\n@q st.relaxed.gpu.global.b64 [%0], %1;\n}"
                 ::"l"(a), "l"(pk(v, tag)), "r"(p) : "memory");
}
__device__ __forceinline__ void st_pk2_p(unsigned long long* a, float v0, float v1, unsigned tag, unsigned p) {
    asm volatile("{\n.reg .pred q;\nsetp.ne.u32 q, %3, 0;\n@q st.relaxed.gpu.global.v2.b64 [%0], {%1, %2};\n}"
                 ::"l"(a), "l"(pk(v0, tag)), "l"(pk(v1, tag)), "r"(p) : "memory");
}
__device__ __forceinline__ void ld_raw2_p(const unsigned long long* a, unsigned long long& u, unsigned long long& v, unsigned p) {
    asm volatile("{\n.reg .pred q;\nsetp.ne.u32 q, %3, 0;\n@q ld.relaxed.gpu.global.v2.b64 {%0, %1}, [%2];\n}"
                 : "+l"(u), "+l"(v) : "l"(a), "r"(p) : "memory");
}
__device__ __forceinline__ float2 ld_pk2_p(const unsigned long long* a, unsigned tag, unsigned p) {
    unsigned long long u = 0, v = 0; unsigned n = 0; bool return_from_spin = false;
    while (true) {
        ld_raw2_p(a, u, v, p);
        if ((pkok(u, tag) && pkok(v, tag)) || p == 0) break;
        if (++n > SPIN_LIMIT) SPIN_FAIL();
        if (return_from_spin) break;
    }
    return make_float2(pkv(u), pkv(v));
}
__device__ __forceinline__ void sts32_p(const float* a, float v, unsigned p) {
    asm volatile("{\n.reg .pred q;\nsetp.ne.u32 q, %2, 0;\n@q st.shared.f32 [%0], %1;\n}" ::"r"(smem_u32(a)), "f"(v), "r"(p) : "memory");
}
__device__ __forceinline__ void sts64_p(const float* a, float v0, float v1, unsigned p) {
    asm volatile("{\n.reg .pred q;\nsetp.ne.u32 q, %3, 0;\n@q st.shared.v2.f32 [%0], {%1, %2};\n}"
                 ::"r"(smem_u32(a)), "f"(v0), "f"(v1), "r"(p) : "memory");
}
__device__ __forceinline__ void sts128_p(const float* a, float v0, float v1, float v2, float v3, unsigned p) {
    asm volatile("{\n.reg .pred q;\nsetp.ne.u32 q, %5, 0;\n@q st.shared.v4.f32 [%0], {%1, %2, %3, %4};\n}"
                 ::"r"(smem_u32(a)), "f"(v0), "f"(v1), "f"(v2), "f"(v3), "r"(p) : "memory");
}

__device__ __forceinline__ float warp_sum(float v) {
#pragma unroll
    for (int o = 16; o > 0; o >>= 1) v += __shfl_xor_sync(0xffffffffu, v, o);
    return v;
}
__device__ __forceinline__ float warp_max(float v) {
#pragma unroll
    for (int o = 16; o > 0; o >>= 1) v = fmaxf(v, __shfl_xor_sync(0xffffffffu, v, o));
    return v;
}

constexpr float LOG2E = 1.4426950408889634f;

__device__ __forceinline__ void ln_stats(const float (&v)[18], float pivot, float& mean_b, float& sd_b) {
    float s0 = 0.f, s1 = 0.f, q0 = 0.f, q1 = 0.f;
#pragma unroll
    for (int k = 0; k < 18; k += 2) {
        const float d0 = v[k] - pivot, d1 = v[k + 1] - pivot;
        s0 += d0; s1 += d1; q0 = fmaf(d0, d0, q0); q1 = fmaf(d1, d1, q1);
    }
    float sm = s0 + s1, sq = q0 + q1;
#pragma unroll
    for (int o = 16; o > 0; o >>= 1) {
        sm += __shfl_xor_sync(0xffffffffu, sm, o);
        sq += __shfl_xor_sync(0xffffffffu, sq, o);
    }
    const float dm = sm * (1.0f / DM);
    const float var = fmaxf(fmaf(-dm, dm, sq * (1.0f / DM)), 0.f);
    mean_b = bfr(pivot + dm);
    float sd;
    asm("sqrt.approx.f32 %0, %1;" : "=f"(sd) : "f"(bfr(bfr(var) + 1e-5f)));
    sd_b = bfr(sd);
}
__device__ __forceinline__ float ln_apply(float x, float mean_b, float sd_b) { return bfr(__fdividef(bfr(x - mean_b), sd_b)); }

__device__ __forceinline__ void ldsm4t(uint32_t (&b)[4], uint32_t a) {
    asm volatile("ldmatrix.sync.aligned.m8n8.x4.trans.shared.b16 {%0,%1,%2,%3}, [%4];"
                 : "=r"(b[0]), "=r"(b[1]), "=r"(b[2]), "=r"(b[3]) : "r"(a));
}
__device__ __forceinline__ void mma_row(float (&c)[4], uint32_t alo, uint32_t ahi, uint32_t b0, uint32_t b1) {
    asm("mma.sync.aligned.m16n8k16.row.col.f32.bf16.bf16.f32 {%0,%1,%2,%3}, {%4,%5,%6,%7}, {%8,%9}, {%0,%1,%2,%3};"
        : "+f"(c[0]), "+f"(c[1]), "+f"(c[2]), "+f"(c[3]) : "r"(alo), "r"(0u), "r"(ahi), "r"(0u), "r"(b0), "r"(b1));
}
__device__ __forceinline__ uint32_t pack_bf(float lo, float hi) {
    return (__float_as_uint(lo) >> 16) | (__float_as_uint(hi) & 0xffff0000u);
}

__device__ __forceinline__ float owner_reduce(const unsigned long long* buf, unsigned tag, float* red, int tid, unsigned live) {
    const int warp = tid >> 5, lane = tid & 31;
    const unsigned act = live && tid < 256;
    const unsigned long long* p = buf + (size_t)(tid & 255) * 4;
    unsigned long long a = 0, b = 0, c = 0, d = 0; unsigned n = 0; bool return_from_spin = false;
    while (true) {
        ld_raw2_p(p, a, b, act);
        ld_raw2_p(p + 2, c, d, act);
        if ((pkok(a, tag) && pkok(b, tag) && pkok(c, tag) && pkok(d, tag)) || !act) break;
        if (++n > SPIN_LIMIT) SPIN_FAIL();
        if (return_from_spin) break;
    }
    float v0 = pkv(a), v1 = pkv(b), v2 = pkv(c), v3 = pkv(d);
#pragma unroll
    for (int o = 2; o <= 16; o <<= 1) {
        v0 += __shfl_xor_sync(0xffffffffu, v0, o);
        v1 += __shfl_xor_sync(0xffffffffu, v1, o);
        v2 += __shfl_xor_sync(0xffffffffu, v2, o);
        v3 += __shfl_xor_sync(0xffffffffu, v3, o);
    }
    sts128_p(red + (warp & 7) * 8 + (lane & 1) * 4, v0, v1, v2, v3, act && lane < 2);
    bar_tail_p(live);
    float s0 = 0.f, s1 = 0.f;
#pragma unroll
    for (int w = 0; w < 8; w += 2) { s0 += red[w * 8 + (tid & 7)]; s1 += red[w * 8 + 8 + (tid & 7)]; }
    return s0 + s1;
}

template <int R, int KS>
__device__ __forceinline__ void slab_mma(uint32_t p0, uint32_t p1, uint32_t p2, uint32_t vaddr, unsigned long long* dst,
                                         int warp, int lane, unsigned tag, unsigned live) {
    uint32_t alo[KS], ahi[KS];
#pragma unroll
    for (int ks = 0; ks < KS; ks++) {
        const uint32_t lo = lds32(vaddr + ks * 32 + (lane & 3) * 4), hi = lds32(vaddr + ks * 32 + 16 + (lane & 3) * 4);
        alo[ks] = lane < 4 ? lo : 0u; ahi[ks] = lane < 4 ? hi : 0u;
    }
    auto row_addr = [&](int r) -> uint32_t {
        if (r >= R) r = 0;
        return (r < 12 ? p0 : (r < 24 ? p1 : p2)) + (r % 12) * WP;
    };
    const uint32_t ra = row_addr(lane) + warp * 128, rb = row_addr(32 + (lane & 15)) + warp * 128 + (lane >> 4) * 16;
    uint32_t b[8][4], b2[4][4];
#pragma unroll
    for (int j = 0; j < 8; j++) ldsm4t(b[j], ra + j * 16);
    if (KS == 3) {
#pragma unroll
        for (int j = 0; j < 4; j++) ldsm4t(b2[j], rb + j * 32);
    }
    float c[8][4];
#pragma unroll
    for (int j = 0; j < 8; j++) { c[j][0] = c[j][1] = c[j][2] = c[j][3] = 0.f; mma_row(c[j], alo[0], ahi[0], b[j][0], b[j][1]); }
#pragma unroll
    for (int j = 0; j < 8; j++) mma_row(c[j], alo[1], ahi[1], b[j][2], b[j][3]);
    if (KS == 3) {
#pragma unroll
        for (int j = 0; j < 8; j++) mma_row(c[j], alo[KS - 1], ahi[KS - 1], b2[j >> 1][(j & 1) * 2], b2[j >> 1][(j & 1) * 2 + 1]);
    }
#pragma unroll
    for (int j = 0; j < 8; j++)
        st_pk2_p(dst + (size_t)(warp * 8 + j) * NCTA * 8 + (lane & 3) * 2, c[j][0], c[j][1], tag, live && lane < 4);
}

__device__ __forceinline__ bool gather_chunk(const unsigned long long* base, int qd, int chunk, unsigned tag, float* gp,
                                             int lane, bool block, unsigned live) {
    unsigned long long o[GC], m = 0, l = 0;
    unsigned n = 0; bool return_from_spin = false;
    const unsigned long long* src = base + (size_t)chunk * GC * PREC;
#pragma unroll
    for (int j = 0; j < GC; j++) o[j] = 0;
    unsigned pend = live ? 0xffffffffu : 0u;
    do {
        ld_raw2_p(src + (size_t)lane * PREC + 128, m, l, (pend >> lane) & 1);
#pragma unroll
        for (int j = 0; j < GC; j++)
            asm volatile("{\n.reg .pred q;\nsetp.ne.u32 q, %2, 0;\n@q ld.relaxed.gpu.global.b64 %0, [%1];\n}"
                         : "+l"(o[j]) : "l"(src + (size_t)j * PREC + qd * 32 + lane), "r"((pend >> j) & 1) : "memory");
        unsigned bad = (pkok(m, tag) && pkok(l, tag)) ? 0u : (1u << lane);
#pragma unroll
        for (int j = 0; j < GC; j++) bad |= pkok(o[j], tag) ? 0u : (1u << j);
        pend &= __reduce_or_sync(0xffffffffu, bad);
        if (pend && !block) return false;
        if (++n > SPIN_LIMIT) SPIN_FAIL();
        if (return_from_spin) break;
    } while (pend);
    const float M = warp_max(pkv(m));
    const float e = pkv(m) == -INFINITY ? 0.f : exp2f((pkv(m) - M) * LOG2E);
    const float L = warp_sum(e * pkv(l));
    float O0 = 0.f, O1 = 0.f;
#pragma unroll
    for (int j = 0; j < GC; j += 2) {
        O0 = fmaf(__shfl_sync(0xffffffffu, e, j), pkv(o[j]), O0);
        O1 = fmaf(__shfl_sync(0xffffffffu, e, j + 1), pkv(o[j + 1]), O1);
    }
    sts32_p(gp + chunk * 36 + lane, O0 + O1, live);
    sts64_p(gp + chunk * 36 + 32, M, L, live && lane == 0);
    return true;
}

__global__ void __launch_bounds__(NTHREADS, 1)
fused_decode_kernel(const __nv_bfloat16* __restrict__ x, const __nv_bfloat16* __restrict__ kc,
                    const __nv_bfloat16* __restrict__ vc, const __nv_bfloat16* __restrict__ wq,
                    const __nv_bfloat16* __restrict__ wo, const __nv_bfloat16* __restrict__ wdown,
                    const __grid_constant__ CUtensorMap map_gate, const __grid_constant__ CUtensorMap map_up,
                    __nv_bfloat16* __restrict__ out) {
    extern __shared__ __align__(1024) unsigned char smem[];
    const uint32_t sb = smem_u32(smem);
    const bool drywarp = DRYRUN && (threadIdx.x >> 5) == 10;
    const int tid = drywarp ? threadIdx.x - 64 : threadIdx.x, warp = tid >> 5, lane = tid & 31;
    const int cta = blockIdx.x;
    const uint32_t bar_full = sb + SM_BAR, bar_empty = bar_full + S * 8;
    const uint32_t bar_pfull = bar_empty + S * 8, bar_pempty = bar_pfull + PS * 8, bar_q = bar_pempty + PS * 8;
    float* s_pr = reinterpret_cast<float*>(smem + SM_PR);
    float* s_gp = reinterpret_cast<float*>(smem + SM_GP);
    float* s_red = reinterpret_cast<float*>(smem + SM_RED);
    float* s_h = reinterpret_cast<float*>(smem + SM_H);
    float* s_hn = reinterpret_cast<float*>(smem + SM_HN);
    float* s_o = reinterpret_cast<float*>(smem + SM_SMALL);
    float* s_hh = s_o + 9 * 32;
    float* s_hown = s_hh + 40;
    volatile int* s_tid = reinterpret_cast<volatile int*>(s_hown + 8);
    volatile int* s_nkv = s_tid + S;
    volatile int* s_gdone = s_nkv + 1;

    if (warp == 9) {
        const unsigned char* kbase = reinterpret_cast<const unsigned char*>(kc);
        const unsigned char* vbase = reinterpret_cast<const unsigned char*>(vc);
        uint64_t pol = 0;
        unsigned ep = 0;
        if (lane == 0) {
#pragma unroll 1
            for (int i = 0; i < 2 * S + 2 * PS + NH; i++) mbar_init(bar_full + i * 8, 1);
            *s_nkv = 0x7fffffff;
            asm volatile("fence.mbarrier_init.release.cluster;" ::: "memory");
            asm volatile("fence.proxy.async.shared::cta;" ::: "memory");
            asm volatile("createpolicy.fractional.L2::evict_first.b64 %0, 1.0;" : "=l"(pol));
#pragma unroll 1
            for (int it = 0; it < DCAP; it++) {
                const int t = it * NCTA + cta;
                s_tid[it] = t;
                mbar_expect_tx(bar_full + it * 8, SLOT_B);
                bulk_load(sb + it * SLOT_B, kbase + (size_t)t * TILE_B, TILE_B, bar_full + it * 8, pol);
                bulk_load(sb + it * SLOT_B + TILE_B, vbase + (size_t)t * TILE_B, TILE_B, bar_full + it * 8, pol);
            }
            ep = *reinterpret_cast<volatile unsigned*>(&g_epoch);
        }
        __syncthreads();
        if (lane == 0) {
            asm volatile("prefetch.tensormap [%0];" ::"l"(&map_gate) : "memory");
            asm volatile("prefetch.tensormap [%0];" ::"l"(&map_up) : "memory");
            unsigned* ctr = &g_ctr[ep & 1][0];
            if (cta == 0) g_ctr[(ep & 1) ^ 1][0] = 0;
            int s = DCAP, sp = 0;
            int use = 0, usep = 0;
            int n = DCAP;
            int tk[LA], tk0[LA];
#pragma unroll
            for (int i = 0; i < LA; i++) { tk[i] = (DCAP + i) * NCTA + cta; tk0[i] = NS * NCTA + (int)atomicAdd(ctr, 1u); }
            auto kv_step = [&](int& t_, int t0_) -> bool {
                const int t = t_;
                if (t >= NTILES) return false;
                if (n + LA < NS) t_ = (n + LA) * NCTA + cta;
                else if (n < NS) t_ = t0_;
                else t_ = NS * NCTA + (int)atomicAdd(ctr, 1u);
                mbar_wait(bar_full + sp * 8, usep & 1);
                if (use > 0) mbar_wait(bar_empty + s * 8, (use - 1) & 1);
                s_tid[s] = t;
                mbar_expect_tx(bar_full + s * 8, SLOT_B);
                bulk_load(sb + s * SLOT_B, kbase + (size_t)t * TILE_B, TILE_B, bar_full + s * 8, pol);
                bulk_load(sb + s * SLOT_B + TILE_B, vbase + (size_t)t * TILE_B, TILE_B, bar_full + s * 8, pol);
                if (++s == S) { s = 0; use++; }
                if (++sp == S) { sp = 0; usep++; }
                n++;
                return true;
            };
            bool more = true;
#pragma unroll 1
            while (more) {
#pragma unroll
                for (int i = 0; i < LA; i++) more = more && kv_step(tk[i], tk0[i]);
            }
            *s_nkv = n;
            {
                int ss = s, su = use;
#pragma unroll 1
                for (int k = 0; k < NW; k++) {
                    mbar_wait(bar_empty + ss * 8, (su - 1) & 1);
                    mbar_arrive(bar_full + ss * 8);
                    if (++ss == S) { ss = 0; su++; }
                }
            }
            const int w0s = s, w0u = use;
#pragma unroll 1
            for (int k = 0; k < NWP; k++) {
                const int pk_ = k - (k < WK1 ? WD1 : DCAPW);
                int sp2 = w0s + pk_, up2 = w0u;
                if (sp2 < 0) { sp2 += S; up2--; } else if (sp2 >= S) { sp2 -= S; up2++; }
                mbar_wait(bar_full + sp2 * 8, (up2 + (pk_ >= 0 && pk_ < NW ? 1 : 0)) & 1);
                mbar_wait(bar_empty + s * 8, (use - 1) & 1);
                const int mat = k / 3, r = k % 3;
                PSTAMP(16 + k);
                if (mat == 0 || mat == 3) {
                    const int rows = (k == 2) ? 8 : 12;
                    const __nv_bfloat16* src = mat == 0 ? wo + ((size_t)cta * 32 + r * 12) * DM : wdown + ((size_t)cta * FC + r * 12) * DM;
                    mbar_expect_tx(bar_full + s * 8, rows * (DM * 2));
#pragma unroll 1
                    for (int i = 0; i < rows; i++) bulk_load(sb + s * SLOT_B + i * WP, src + (size_t)i * DM, DM * 2, bar_full + s * 8, pol);
                } else {
                    mbar_expect_tx(bar_full + s * 8, 192 * FCP * 2);
                    tma_load_2d(sb + s * SLOT_B, mat == 1 ? &map_gate : &map_up, (cta * FC) & ~7, r * 192, bar_full + s * 8);
                }
                if (++s == S) { s = 0; use++; }
            }
        }
        return;
    }

    unsigned short xo = 0;
    unsigned tag = 0;
    if (drywarp) {
        __syncthreads();
        mbar_wait(bar_q + 8 * 8, 0);
    } else {
    STAMP(0);
    unsigned short xr[18], xq[8];
#pragma unroll
    for (int k = 0; k < 18; k++)
        asm volatile("ld.global.nc.u16 %0, [%1];" : "=h"(xr[k]) : "l"(x + lane + 32 * k));
#pragma unroll
    for (int k = 0; k < 8; k++)
        asm volatile("ld.global.nc.u16 %0, [%1];" : "=h"(xq[k]) : "l"(x + (tid >> 2) + 72 * k));
    asm volatile("ld.global.nc.u16 %0, [%1];" : "=h"(xo) : "l"(x + (cta < NOWN ? cta : 0) * 8 + (tid & 7)));
    tag = *reinterpret_cast<volatile unsigned*>(&g_epoch) + 1u;
    uint4 wv[8];
    {
        const int ch = tid & 3, rg = tid >> 2;
        const uint4* wp = reinterpret_cast<const uint4*>(wq + (size_t)rg * (NH * DH) + cta * 32 + ch * 8);
#pragma unroll
        for (int k = 0; k < 8; k++)
            asm volatile("ld.global.nc.L1::no_allocate.v4.u32 {%0,%1,%2,%3}, [%4];"
                         : "=r"(wv[k].x), "=r"(wv[k].y), "=r"(wv[k].z), "=r"(wv[k].w)
                         : "l"(wp + (size_t)k * 72 * (NH * DH / 8)));
    }
    {
        if (tid < 16) st_pk2(g_q + cta * 32 + tid * 2, 0.f, 0.f, 0u);
        if (tid < 2 * (PREC / 2)) {
            const int hl = tid / (PREC / 2), j = tid % (PREC / 2);
            st_pk2(g_part + ((size_t)(NH - 2 + hl) * NCTA + cta) * PREC + 2 * j, 0.f, 0.f, 0u);
        }
        st_pk2(g_y + ((size_t)(tid >> 2) * NCTA + cta) * 8 + (tid & 3) * 2, 0.f, 0.f, 0u);
        st_pk2(g_z + ((size_t)(tid >> 2) * NCTA + cta) * 8 + (tid & 3) * 2, 0.f, 0.f, 0u);
        if (cta < NOWN && tid < 4) st_pk2(g_h + cta * 8 + tid * 2, 0.f, 0.f, 0u);
    }
    __syncthreads();
    {
        float xv[18];
#pragma unroll
        for (int k = 0; k < 18; k++) xv[k] = bflo(xr[k]);
        float mean_b, sd_b;
        ln_stats(xv, __shfl_sync(0xffffffffu, xv[0], 0), mean_b, sd_b);
        float xn[8];
#pragma unroll
        for (int k = 0; k < 8; k++) xn[k] = ln_apply(bflo(xq[k]), mean_b, sd_b);
        STAMPD(15, wv[0].x ^ wv[1].x ^ wv[2].x ^ wv[3].x ^ wv[4].x ^ wv[5].x ^ wv[6].x ^ wv[7].x);
        float acc[8];
#pragma unroll
        for (int e = 0; e < 8; e++) acc[e] = 0.f;
#pragma unroll
        for (int k = 0; k < 8; k++) {
            acc[0] = fmaf(xn[k], bflo(wv[k].x), acc[0]); acc[1] = fmaf(xn[k], bfhi(wv[k].x), acc[1]);
            acc[2] = fmaf(xn[k], bflo(wv[k].y), acc[2]); acc[3] = fmaf(xn[k], bfhi(wv[k].y), acc[3]);
            acc[4] = fmaf(xn[k], bflo(wv[k].z), acc[4]); acc[5] = fmaf(xn[k], bfhi(wv[k].z), acc[5]);
            acc[6] = fmaf(xn[k], bflo(wv[k].w), acc[6]); acc[7] = fmaf(xn[k], bfhi(wv[k].w), acc[7]);
        }
        {
            const bool up = lane & 16;
#pragma unroll
            for (int e = 0; e < 4; e++) {
                const float snd = up ? acc[e] : acc[e + 4], kp = up ? acc[e + 4] : acc[e];
                acc[e] = kp + __shfl_xor_sync(0xffffffffu, snd, 16);
            }
        }
        {
            const bool up = lane & 8;
#pragma unroll
            for (int e = 0; e < 2; e++) {
                const float snd = up ? acc[e] : acc[e + 2], kp = up ? acc[e + 2] : acc[e];
                acc[e] = kp + __shfl_xor_sync(0xffffffffu, snd, 8);
            }
        }
        {
            const bool up = lane & 4;
            const float snd = up ? acc[0] : acc[1], kp = up ? acc[1] : acc[0];
            acc[0] = kp + __shfl_xor_sync(0xffffffffu, snd, 4);
        }
        const int col = (lane & 3) * 8 + ((lane >> 4) & 1) * 4 + ((lane >> 3) & 1) * 2 + ((lane >> 2) & 1);
        s_red[warp * 32 + col] = acc[0];
    }
    bar_tail();
    STAMP(11);
    if (tid < 32) {
        float s = 0.f;
#pragma unroll
        for (int w = 0; w < 9; w++) s += s_red[w * 32 + tid];
        st_pk1_p(g_q + cta * 32 + tid, bfr(s), tag, 1u);
    }
    STAMP(1);
    }

    const unsigned long long* gbase = g_part + (size_t)(cta >> 2) * NCTA * PREC;
    {
    unsigned live;
    asm volatile("mov.u32 %0, %1;" : "=r"(live) : "r"(drywarp ? 0 : 1));

    if (warp < NW) {
        const int half = lane >> 4, c = lane & 15;
        const uint32_t loff = half * 256 + c * 16;
        int slot = warp, use = 0;
#pragma unroll 1
        for (int it = warp;; it += NW) {
            int head = -1;
            {
                unsigned n = 0; bool return_from_spin = false;
                while (it < *s_nkv) {
                    if (mbar_try(bar_full + slot * 8, use & 1)) { if (it < *s_nkv) head = s_tid[slot] >> 9; break; }
                    if (++n > SPIN_LIMIT) SPIN_FAIL();
                    if (return_from_spin) break;
                }
            }
            const int ps = it % PS;
            float* pp = s_pr + ps * PREC;
            if (head < 0) {
                if (it == *s_nkv) {
                    if (it >= PS) mbar_wait(bar_pempty + ps * 8, ((it / PS) - 1) & 1);
                    if (lane == 0) { reinterpret_cast<int*>(pp)[130] = -1; mbar_arrive(bar_pfull + ps * 8); }
                }
                break;
            }
            mbar_wait(bar_q + head * 8, 0);
            float qf[8];
            {
                const uint4 qq = lds128(sb + SM_Q + head * (DH * 2) + c * 16);
                qf[0] = bflo(qq.x); qf[1] = bfhi(qq.x); qf[2] = bflo(qq.y); qf[3] = bfhi(qq.y);
                qf[4] = bflo(qq.z); qf[5] = bfhi(qq.z); qf[6] = bflo(qq.w); qf[7] = bfhi(qq.w);
            }
            const uint32_t kaddr = sb + slot * SLOT_B + loff;
            float s[16];
#pragma unroll
            for (int j = 0; j < 16; j++) {
                const uint4 kv = lds128(kaddr + j * 512);
                float d0 = qf[0] * bflo(kv.x), d1 = qf[1] * bfhi(kv.x);
                d0 = fmaf(qf[2], bflo(kv.y), d0); d1 = fmaf(qf[3], bfhi(kv.y), d1);
                d0 = fmaf(qf[4], bflo(kv.z), d0); d1 = fmaf(qf[5], bfhi(kv.z), d1);
                d0 = fmaf(qf[6], bflo(kv.w), d0); d1 = fmaf(qf[7], bfhi(kv.w), d1);
                s[j] = d0 + d1;
            }
            {
                const bool up = c & 8;
#pragma unroll
                for (int j = 0; j < 8; j++) {
                    const float snd = up ? s[j] : s[j + 8], kp = up ? s[j + 8] : s[j];
                    s[j] = kp + __shfl_xor_sync(0xffffffffu, snd, 8);
                }
            }
            {
                const bool up = c & 4;
#pragma unroll
                for (int j = 0; j < 4; j++) {
                    const float snd = up ? s[j] : s[j + 4], kp = up ? s[j + 4] : s[j];
                    s[j] = kp + __shfl_xor_sync(0xffffffffu, snd, 4);
                }
            }
            {
                const bool up = c & 2;
#pragma unroll
                for (int j = 0; j < 2; j++) {
                    const float snd = up ? s[j] : s[j + 2], kp = up ? s[j + 2] : s[j];
                    s[j] = kp + __shfl_xor_sync(0xffffffffu, snd, 2);
                }
            }
            {
                const bool up = c & 1;
                const float snd = up ? s[0] : s[1], kp = up ? s[1] : s[0];
                s[0] = kp + __shfl_xor_sync(0xffffffffu, snd, 1);
            }
            const float sc = bfr(bfr(s[0]) * 0.08838834764831845f);
            const float m = warp_max(sc);
            const float p = exp2f((sc - m) * LOG2E);
            float acc[8];
#pragma unroll
            for (int e = 0; e < 8; e++) acc[e] = 0.f;
            const uint32_t vaddr = kaddr + TILE_B;
#pragma unroll
            for (int j = 0; j < 16; j++) {
                const uint4 vv = lds128(vaddr + j * 512);
                const float pj = __shfl_sync(0xffffffffu, p, (lane & 16) + j);
                acc[0] = fmaf(pj, bflo(vv.x), acc[0]); acc[1] = fmaf(pj, bfhi(vv.x), acc[1]);
                acc[2] = fmaf(pj, bflo(vv.y), acc[2]); acc[3] = fmaf(pj, bfhi(vv.y), acc[3]);
                acc[4] = fmaf(pj, bflo(vv.z), acc[4]); acc[5] = fmaf(pj, bfhi(vv.z), acc[5]);
                acc[6] = fmaf(pj, bflo(vv.w), acc[6]); acc[7] = fmaf(pj, bfhi(vv.w), acc[7]);
            }
            __syncwarp();
            if (lane == 0) mbar_arrive(bar_empty + slot * 8);
            slot += NW; if (slot >= S) { slot -= S; use++; }
            float r4[4];
#pragma unroll
            for (int e = 0; e < 4; e++) {
                const float snd = half ? acc[e] : acc[e + 4], kp = half ? acc[e + 4] : acc[e];
                r4[e] = kp + __shfl_xor_sync(0xffffffffu, snd, 16);
            }
            const float l = warp_sum(p);
            if (it >= PS) mbar_wait(bar_pempty + ps * 8, ((it / PS) - 1) & 1);
            *reinterpret_cast<float4*>(pp + c * 8 + half * 4) = make_float4(r4[0], r4[1], r4[2], r4[3]);
            if (lane == 0) *reinterpret_cast<float4*>(pp + 128) = make_float4(m, l, __int_as_float(head), 0.f);
            __syncwarp();
            if (lane == 0) mbar_arrive(bar_pfull + ps * 8);
        }
    } else if (live && warp == 8) {
        int qn = 0;
        auto fetch_q = [&]() {
            const unsigned long long* src = g_q + qn * DH + lane * 4;
            unsigned long long a[8], b[8]; unsigned n = 0; bool return_from_spin = false;
            while (true) {
                bool ok = true;
#pragma unroll
                for (int j = 0; j < 4; j++) { ld_raw2(src + j * DH, a[2 * j], b[2 * j]); ld_raw2(src + j * DH + 2, a[2 * j + 1], b[2 * j + 1]); }
#pragma unroll
                for (int j = 0; j < 8; j++) ok = ok && pkok(a[j], tag) && pkok(b[j], tag);
                if (ok) break;
                if (++n > SPIN_LIMIT) SPIN_FAIL();
                if (return_from_spin) break;
            }
#pragma unroll
            for (int j = 0; j < 4; j++)
                *reinterpret_cast<uint2*>(smem + SM_Q + (qn + j) * (DH * 2) + lane * 8) =
                    make_uint2(((unsigned)a[2 * j] >> 16) | ((unsigned)b[2 * j] & 0xffff0000u),
                               ((unsigned)a[2 * j + 1] >> 16) | ((unsigned)b[2 * j + 1] & 0xffff0000u));
            __syncwarp();
            if (lane < 4) mbar_arrive(bar_q + (qn + lane) * 8);
            qn += 4;
        };
        fetch_q();
        int gdone = 0;
        int cur = 0;
        float M = -INFINITY, L = 0.f, a0 = 0.f, a1 = 0.f, a2 = 0.f, a3 = 0.f;
#pragma unroll 1
        for (int it = 0;; it++) {
            const int ps = it % PS;
            while (qn < NH && (qn < cur + 4 || !mbar_test(bar_pfull + ps * 8, (it / PS) & 1))) fetch_q();
            if (cur > (cta >> 2) + 1) {
                while (gdone < NGC && !mbar_test(bar_pfull + ps * 8, (it / PS) & 1)) {
                    if (!gather_chunk(gbase, cta & 3, gdone, tag, s_gp, lane, false, 1u)) break;
                    gdone++;
                }
            }
            mbar_wait(bar_pfull + ps * 8, (it / PS) & 1);
            const float* pp = s_pr + ps * PREC;
            const float4 v = *reinterpret_cast<const float4*>(pp + lane * 4);
            const float4 ml = *reinterpret_cast<const float4*>(pp + 128);
            __syncwarp();
            if (lane == 0) mbar_arrive(bar_pempty + ps * 8);
            int head = __float_as_int(ml.z);
            if (head < 0) head = NH;
#pragma unroll 1
            for (; cur < head; cur++) {
                unsigned long long* dst = g_part + ((size_t)cur * NCTA + cta) * PREC;
                st_pk2(dst + lane * 4, a0, a1, tag);
                st_pk2(dst + lane * 4 + 2, a2, a3, tag);
                if (lane == 0) st_pk2(dst + 128, M, L, tag);
                M = -INFINITY; L = 0.f; a0 = a1 = a2 = a3 = 0.f;
            }
            if (head == NH) break;
            const float Mn = fmaxf(M, ml.x);
            const float ea = exp2f((M - Mn) * LOG2E), eb = exp2f((ml.x - Mn) * LOG2E);
            M = Mn;
            L = L * ea + ml.y * eb;
            a0 = a0 * ea + v.x * eb; a1 = a1 * ea + v.y * eb; a2 = a2 * ea + v.z * eb; a3 = a3 * ea + v.w * eb;
        }
        if (lane == 0) *s_gdone = gdone;
    }
    bar_tail_p(live);
    STAMP(2);
    const int nkv = live ? *s_nkv : 0;
    const int w0s = nkv % S, w0u = nkv / S;
    auto piece = [&](int k) -> uint32_t { int ps = w0s + k; if (ps >= S) ps -= S; return sb + ps * SLOT_B; };
    auto piece_wait = [&](int k0, int cnt) {
        const int k = k0 + (lane < cnt ? lane : 0);
        int ps = w0s + k, pu = w0u; if (ps >= S) { ps -= S; pu++; }
        mbar_wait_p(bar_full + ps * 8, (pu + (k < NW ? 1 : 0)) & 1, live);
    };
    if (warp == 8) piece_wait(0, 3);
#pragma unroll 1
    for (int ch = (live ? *s_gdone : 0) + (live ? warp : 0); ch < (live ? NGC : 1); ch += 9)
        gather_chunk(gbase, cta & 3, ch, tag, s_gp, lane, true, live);
    bar_tail_p(live);
    STAMP(3);
    {
        float M = s_gp[32];
#pragma unroll
        for (int j = 1; j < NGC; j++) M = fmaxf(M, s_gp[j * 36 + 32]);
        float o0 = 0.f, o1 = 0.f, L = 0.f;
#pragma unroll
        for (int j = 0; j < NGC; j++) {
            const float2 ml = *reinterpret_cast<const float2*>(s_gp + j * 36 + 32);
            const float e = ml.x == -INFINITY ? 0.f : exp2f((ml.x - M) * LOG2E);
            L = fmaf(e, ml.y, L);
            if (j & 1) o1 = fmaf(e, s_gp[j * 36 + lane], o1); else o0 = fmaf(e, s_gp[j * 36 + lane], o0);
        }
        const float o = bfr(__fdividef(o0 + o1, L));
        const float on = __shfl_down_sync(0xffffffffu, o, 1);
        sts32_p(s_o + warp * 32 + (lane >> 1), __uint_as_float(pack_bf(o, on)), live && !(lane & 1));
        __syncwarp();
    }
    STAMP(12);
    slab_mma<32, 2>(piece(0), piece(1), piece(2), smem_u32(s_o + warp * 32), g_y + (size_t)cta * 8, warp, lane, tag, live);
    STAMP(4);
    if (cta < NOWN) {
        const float s = owner_reduce(g_y + (size_t)cta * NCTA * 8, tag, s_red, tid, live);
        const float h = bfr(bflo(xo) + bfr(s));
        st_pk1_p(g_h + cta * 8 + (tid & 7), h, tag, live && tid < 8);
        sts32_p(s_hown + (tid & 7), h, live && tid < 8);
    }
    STAMP(5);
    if (warp == 8) piece_wait(3, 6);
    {
        const float2 v = ld_pk2_p(g_h + 2 * tid, tag, live);
        sts64_p(s_h + 2 * tid, v.x, v.y, live);
        bar_tail_p(live);
    }
    STAMP(6);
    {
        float hv[18];
#pragma unroll
        for (int k = 0; k < 18; k++) hv[k] = s_h[lane + 32 * k];
        float mean_b, sd_b;
        ln_stats(hv, __shfl_sync(0xffffffffu, hv[0], 0), mean_b, sd_b);
        const float2 hh2 = *reinterpret_cast<const float2*>(s_h + 2 * tid);
        const float n0 = ln_apply(hh2.x, mean_b, sd_b), n1 = ln_apply(hh2.y, mean_b, sd_b);
        sts32_p(s_hn + tid, __uint_as_float(pack_bf(n0, n1)), live);
    }
    bar_tail_p(live);
    STAMP(7);
    {
        uint32_t af[4][2];
#pragma unroll
        for (int ks = 0; ks < 4; ks++) {
            const uint32_t a = sb + SM_HN + (warp * 64 + ks * 16 + (lane & 3) * 2) * 2;
            const uint32_t lo = lds32(a), hi = lds32(a + 16);
            af[ks][0] = lane < 4 ? lo : 0u; af[ks][1] = lane < 4 ? hi : 0u;
        }
        const uint32_t roff = ((warp % 3) * 64 + lane) * (FCP * 2);
        uint32_t b[2][5][2][4];
#pragma unroll
        for (int mat = 0; mat < 2; mat++) {
            const uint32_t base = piece(3 + mat * 3 + warp / 3) + roff;
#pragma unroll
            for (int nt = 0; nt < 5; nt++) {
                ldsm4t(b[mat][nt][0], base + nt * 16);
                ldsm4t(b[mat][nt][1], base + 32 * (FCP * 2) + nt * 16);
            }
        }
        float c[2][5][4];
#pragma unroll
        for (int ks = 0; ks < 4; ks++)
#pragma unroll
            for (int mat = 0; mat < 2; mat++)
#pragma unroll
                for (int nt = 0; nt < 5; nt++) {
                    if (ks == 0) c[mat][nt][0] = c[mat][nt][1] = c[mat][nt][2] = c[mat][nt][3] = 0.f;
                    mma_row(c[mat][nt], af[ks][0], af[ks][1], b[mat][nt][ks >> 1][(ks & 1) * 2], b[mat][nt][ks >> 1][(ks & 1) * 2 + 1]);
                }
#pragma unroll
        for (int mat = 0; mat < 2; mat++)
#pragma unroll
            for (int nt = 0; nt < 5; nt++)
                sts64_p(s_red + warp * 80 + mat * 40 + nt * 8 + (lane & 3) * 2, c[mat][nt][0], c[mat][nt][1], live && lane < 4);
    }
    bar_tail_p(live);
    if (warp == 8) piece_wait(9, 3);
    if (tid < 64 || !live) {
        const int col = (live ? tid : lane) < FC ? (live ? tid : lane) : 0;
        const float* pr = s_red + col + (cta & 1) * 4;
        float g0 = pr[0], g1 = 0.f, u0 = pr[40], u1 = 0.f;
#pragma unroll
        for (int w = 1; w < 9; w += 2) {
            g1 += pr[w * 80]; u1 += pr[w * 80 + 40];
            g0 += pr[w * 80 + 80]; u0 += pr[w * 80 + 120];
        }
        const float g = bfr(g0 + g1), u = bfr(u0 + u1);
        const float inner = 0.7978845608028654f * (g + 0.044715f * g * g * g);
        const float ge = bfr(0.5f * g * (1.0f + tanhf(inner)));
        const float hh = tid < FC ? bfr(ge * u) : 0.f;
        const float hn2 = __shfl_down_sync(0xffffffffu, hh, 1);
        sts32_p(s_hh + (tid >> 1), __uint_as_float(pack_bf(hh, hn2)), live && !(tid & 1) && tid < 48);
    }
    bar_tail_p(live);
    STAMP(8);
    slab_mma<FC, 3>(piece(9), piece(10), piece(11), smem_u32(s_hh), g_z + (size_t)cta * 8, warp, lane, tag, live);
    STAMP(9);
    if (cta < NOWN) {
        const float s = owner_reduce(g_z + (size_t)cta * NCTA * 8, tag, s_red, tid, live);
        const unsigned short r = __bfloat16_as_ushort(__float2bfloat16_rn(s_hown[tid & 7] + bfr(s)));
        asm volatile("{\n.reg .pred q;\nsetp.ne.u32 q, %2, 0;\n@q st.global.u16 [%0], %1;\n}"
                     ::"l"(out + cta * 8 + (tid & 7)), "h"(r), "r"((unsigned)(live && tid < 8)) : "memory");
        asm volatile("{\n.reg .pred q;\nsetp.ne.u32 q, %2, 0;\n@q st.relaxed.gpu.global.u32 [%0], %1;\n}"
                     ::"l"(&g_epoch), "r"(tag), "r"((unsigned)(live && cta == 0 && tid == 0)) : "memory");
    }
    STAMP(10);
    }
}

typedef CUresult (*PFN_encodeTiled)(CUtensorMap*, CUtensorMapDataType, cuuint32_t, void*, const cuuint64_t*,
                                    const cuuint64_t*, const cuuint32_t*, const cuuint32_t*, CUtensorMapInterleave,
                                    CUtensorMapSwizzle, CUtensorMapL2promotion, CUtensorMapFloatOOBfill);

void make_map(PFN_encodeTiled enc, CUtensorMap* m, const void* ptr) {
    cuuint64_t dims[2] = {(cuuint64_t)DFF, (cuuint64_t)DM};
    cuuint64_t strides[1] = {(cuuint64_t)DFF * 2};
    cuuint32_t box[2] = {(cuuint32_t)FCP, 192u};
    cuuint32_t estr[2] = {1u, 1u};
    enc(m, CU_TENSOR_MAP_DATA_TYPE_BFLOAT16, 2, const_cast<void*>(ptr), dims, strides, box, estr,
        CU_TENSOR_MAP_INTERLEAVE_NONE, CU_TENSOR_MAP_SWIZZLE_NONE, CU_TENSOR_MAP_L2_PROMOTION_L2_128B,
        CU_TENSOR_MAP_FLOAT_OOB_FILL_NONE);
}

}

extern "C" void kernel_launch(void* const* d_in, const int* in_sizes, int n_in, void* d_out, int out_size) {
    (void)in_sizes; (void)n_in; (void)out_size;
    static PFN_encodeTiled enc = nullptr;
    if (!enc) {
        void* fn = nullptr;
        cudaDriverEntryPointQueryResult st;
        cudaGetDriverEntryPoint("cuTensorMapEncodeTiled", &fn, cudaEnableDefault, &st);
        enc = reinterpret_cast<PFN_encodeTiled>(fn);
        cudaFuncSetAttribute(fused_decode_kernel, cudaFuncAttributeMaxDynamicSharedMemorySize, SM_TOTAL);
    }
    CUtensorMap mg, mu;
    make_map(enc, &mg, d_in[6]);
    make_map(enc, &mu, d_in[7]);
    fused_decode_kernel<<<NCTA, NTHREADS, SM_TOTAL>>>(
        (const __nv_bfloat16*)d_in[0], (const __nv_bfloat16*)d_in[1], (const __nv_bfloat16*)d_in[2],
        (const __nv_bfloat16*)d_in[3], (const __nv_bfloat16*)d_in[4], (const __nv_bfloat16*)d_in[8], mg, mu,
        (__nv_bfloat16*)d_out);
}
```

```cpp
#include <cuda_runtime.h>
#include <cuda_bf16.h>
#include <cuda.h>
#include <stdint.h>

namespace {

constexpr int DM = 576;
constexpr int NH = 32;
constexpr int SK = 16384;
constexpr int DH = 128;
constexpr int DFF = 4608;

constexpr int NCTA = 128;
constexpr int TK = 32;
constexpr int TILE_B = TK * DH * 2;
constexpr int SLOT_B = 2 * TILE_B;
constexpr int NTILES = NH * (SK / TK);
#define LA_ 4
constexpr int LA = LA_;
constexpr int S = 12;
#define DCAP_ 4
constexpr int DCAP = DCAP_;
#define DCAPW_ 2
constexpr int DCAPW = DCAPW_;
#define WK1 0
#define WD1 1
#define NSX_ 2
constexpr int NS = DCAP + NSX_ * LA;
#define NW_ 8
constexpr int NW = NW_;
constexpr int PS = 16;
constexpr int NTAIL = 288;
constexpr int NTHREADS = 320;
constexpr int NWP = 12;
constexpr int FC = DFF / NCTA;
constexpr int FCP = 40;
constexpr int WP = DM * 2 + 16;
constexpr int NOWN = 72;
constexpr int GC = 32;
constexpr int NGC = NCTA / GC;
constexpr int PREC = 132;

static_assert(S >= NW + DCAP, "parity aliasing");
static_assert(NWP <= S && DCAPW <= DCAP && PS >= NW, "ring");

constexpr int SM_Q = S * SLOT_B;
constexpr int SM_PR = SM_Q + NH * DH * 2;
constexpr int SM_GP = SM_PR + PS * PREC * 4;
constexpr int SM_RED = SM_GP + NGC * 36 * 4;
constexpr int SM_H = SM_RED + 16 * 72 * 4;
constexpr int SM_HN = SM_H + DM * 4;
constexpr int SM_SMALL = SM_HN + DM * 4;
constexpr int SM_BAR = SM_SMALL + 9 * 32 * 4 + 64 * 4;
constexpr int SM_TOTAL = SM_BAR + (2 * S + 2 * PS + NH) * 8;
static_assert(SM_TOTAL <= 232448, "smem");

__device__ unsigned int g_epoch;
__device__ unsigned int g_ctr[2][32];
__device__ __align__(16) unsigned long long g_q[NH * DH];
__device__ __align__(16) unsigned long long g_part[NH * NCTA * PREC];
__device__ __align__(16) unsigned long long g_y[NOWN * NCTA * 8];
__device__ __align__(16) unsigned long long g_h[DM];
__device__ __align__(16) unsigned long long g_z[NOWN * NCTA * 8];
#define STAMP(i)
#define STAMPD(i, dep)
#define PSTAMP(i)

constexpr unsigned SPIN_LIMIT = 1u << 22;
#define SPIN_FAIL() __trap()

__device__ __forceinline__ uint32_t smem_u32(const void* p) { return (uint32_t)__cvta_generic_to_shared(p); }
__device__ __forceinline__ void mbar_init(uint32_t bar, uint32_t cnt) {
    asm volatile("mbarrier.init.shared::cta.b64 [%0], %1;" ::"r"(bar), "r"(cnt) : "memory");
}
__device__ __forceinline__ void mbar_expect_tx(uint32_t bar, uint32_t bytes) {
    asm volatile("mbarrier.arrive.expect_tx.shared::cta.b64 _, [%0], %1;" ::"r"(bar), "r"(bytes) : "memory");
}
__device__ __forceinline__ void mbar_arrive(uint32_t bar) {
    asm volatile("mbarrier.arrive.shared::cta.b64 _, [%0];" ::"r"(bar) : "memory");
}
__device__ __forceinline__ bool mbar_try(uint32_t bar, uint32_t parity) {
    uint32_t ok;
    asm volatile("{\n.reg .pred p;\nmbarrier.try_wait.parity.shared::cta.b64 p, [%1], %2;\nselp.u32 %0, 1, 0, p;\n}\n"
                 : "=r"(ok) : "r"(bar), "r"(parity) : "memory");
    return ok != 0;
}
__device__ __forceinline__ bool mbar_test(uint32_t bar, uint32_t parity) {
    uint32_t ok;
    asm volatile("{\n.reg .pred p;\nmbarrier.test_wait.parity.shared::cta.b64 p, [%1], %2;\nselp.u32 %0, 1, 0, p;\n}\n"
                 : "=r"(ok) : "r"(bar), "r"(parity) : "memory");
    return ok != 0;
}
__device__ __forceinline__ void mbar_wait(uint32_t bar, uint32_t parity) {
    unsigned n = 0; bool return_from_spin = false;
    while (!mbar_try(bar, parity)) {
        if (++n > SPIN_LIMIT) SPIN_FAIL();
        if (return_from_spin) break;
    }
}
__device__ __forceinline__ void bulk_load(uint32_t dst, const void* src, uint32_t bytes, uint32_t bar, uint64_t pol) {
    asm volatile("cp.async.bulk.shared::cluster.global.mbarrier::complete_tx::bytes.L2::cache_hint [%0], [%1], %2, [%3], %4;"
                 ::"r"(dst), "l"(src), "r"(bytes), "r"(bar), "l"(pol) : "memory");
}
__device__ __forceinline__ void l2_prefetch(const void* src, uint32_t bytes) {
    asm volatile("cp.async.bulk.prefetch.L2.global [%0], %1;" ::"l"(src), "r"(bytes) : "memory");
}
__device__ __forceinline__ void tma_load_2d(uint32_t dst, const CUtensorMap* map, int c0, int c1, uint32_t bar) {
    asm volatile("cp.async.bulk.tensor.2d.shared::cluster.global.mbarrier::complete_tx::bytes [%0], [%1, {%3, %4}], [%2];"
                 ::"r"(dst), "l"(map), "r"(bar), "r"(c0), "r"(c1) : "memory");
}
__device__ __forceinline__ void bar_tail() { asm volatile("bar.sync 1, 288;" ::: "memory"); }

__device__ __forceinline__ uint4 lds128(uint32_t a) {
    uint4 v; asm volatile("ld.shared.v4.u32 {%0,%1,%2,%3}, [%4];" : "=r"(v.x), "=r"(v.y), "=r"(v.z), "=r"(v.w) : "r"(a)); return v;
}
__device__ __forceinline__ uint2 lds64(uint32_t a) {
    uint2 v; asm volatile("ld.shared.v2.u32 {%0,%1}, [%2];" : "=r"(v.x), "=r"(v.y) : "r"(a)); return v;
}
__device__ __forceinline__ uint32_t lds32(uint32_t a) {
    uint32_t v; asm volatile("ld.shared.u32 %0, [%1];" : "=r"(v) : "r"(a)); return v;
}
__device__ __forceinline__ float bflo(uint32_t w) { return __uint_as_float(w << 16); }
__device__ __forceinline__ float bfhi(uint32_t w) { return __uint_as_float(w & 0xffff0000u); }
__device__ __forceinline__ float bfr(float x) { return __bfloat162float(__float2bfloat16_rn(x)); }

__device__ __forceinline__ unsigned long long pk(float v, unsigned tag) {
    return ((unsigned long long)tag << 32) | (unsigned long long)__float_as_uint(v);
}
__device__ __forceinline__ float pkv(unsigned long long a) { return __uint_as_float((unsigned)a); }
__device__ __forceinline__ bool pkok(unsigned long long a, unsigned tag) { return (unsigned)(a >> 32) == tag; }
__device__ __forceinline__ void st_pk2(unsigned long long* p, float v0, float v1, unsigned tag) {
    asm volatile("st.relaxed.gpu.global.v2.b64 [%0], {%1, %2};" ::"l"(p), "l"(pk(v0, tag)), "l"(pk(v1, tag)) : "memory");
}
__device__ __forceinline__ void ld_raw2(const unsigned long long* p, unsigned long long& a, unsigned long long& b) {
    asm volatile("ld.relaxed.gpu.global.v2.b64 {%0, %1}, [%2];" : "=l"(a), "=l"(b) : "l"(p) : "memory");
}

__device__ __forceinline__ void bar_tail_p(unsigned p) {
    asm volatile("{\n.reg .pred q;\nsetp.ne.u32 q, %0, 0;\n@q bar.sync 1, 288;\n}" ::"r"(p) : "memory");
}
__device__ __forceinline__ void mbar_wait_p(uint32_t bar, uint32_t parity, unsigned p) {
    unsigned n = 0, ok; bool return_from_spin = false;
    do {
        asm volatile("{\n.reg .pred q, r;\nsetp.ne.u32 q, %3, 0;\nsetp.eq.u32 r, %3, 0;\n"
                     "@q mbarrier.try_wait.parity.shared::cta.b64 r, [%1], %2;\nselp.u32 %0, 1, 0, r;\n}"
                     : "=r"(ok) : "r"(bar), "r"(parity), "r"(p) : "memory");
        if (++n > SPIN_LIMIT) SPIN_FAIL();
        if (return_from_spin) break;
    } while (!ok);
}
__device__ __forceinline__ void st_pk1_p(unsigned long long* a, float v, unsigned tag, unsigned p) {
    asm volatile("{\n.reg .pred q;\nsetp.ne.u32 q, %2, 0;\n@q st.relaxed.gpu.global.b64 [%0], %1;\n}"
                 ::"l"(a), "l"(pk(v, tag)), "r"(p) : "memory");
}
__device__ __forceinline__ void st_pk2_p(unsigned long long* a, float v0, float v1, unsigned tag, unsigned p) {
    asm volatile("{\n.reg .pred q;\nsetp.ne.u32 q, %3, 0;\n@q st.relaxed.gpu.global.v2.b64 [%0], {%1, %2};\n}"
                 ::"l"(a), "l"(pk(v0, tag)), "l"(pk(v1, tag)), "r"(p) : "memory");
}
__device__ __forceinline__ void ld_raw2_p(const unsigned long long* a, unsigned long long& u, unsigned long long& v, unsigned p) {
    asm volatile("{\n.reg .pred q;\nsetp.ne.u32 q, %3, 0;\n@q ld.relaxed.gpu.global.v2.b64 {%0, %1}, [%2];\n}"
                 : "+l"(u), "+l"(v) : "l"(a), "r"(p) : "memory");
}
__device__ __forceinline__ float2 ld_pk2_p(const unsigned long long* a, unsigned tag, unsigned p) {
    unsigned long long u = 0, v = 0; unsigned n = 0; bool return_from_spin = false;
    while (true) {
        ld_raw2_p(a, u, v, p);
        if ((pkok(u, tag) && pkok(v, tag)) || p == 0) break;
        if (++n > SPIN_LIMIT) SPIN_FAIL();
        if (return_from_spin) break;
    }
    return make_float2(pkv(u), pkv(v));
}
__device__ __forceinline__ void sts32_p(const float* a, float v, unsigned p) {
    asm volatile("{\n.reg .pred q;\nsetp.ne.u32 q, %2, 0;\n@q st.shared.f32 [%0], %1;\n}" ::"r"(smem_u32(a)), "f"(v), "r"(p) : "memory");
}
__device__ __forceinline__ void sts64_p(const float* a, float v0, float v1, unsigned p) {
    asm volatile("{\n.reg .pred q;\nsetp.ne.u32 q, %3, 0;\n@q st.shared.v2.f32 [%0], {%1, %2};\n}"
                 ::"r"(smem_u32(a)), "f"(v0), "f"(v1), "r"(p) : "memory");
}
__device__ __forceinline__ void sts128_p(const float* a, float v0, float v1, float v2, float v3, unsigned p) {
    asm volatile("{\n.reg .pred q;\nsetp.ne.u32 q, %5, 0;\n@q st.shared.v4.f32 [%0], {%1, %2, %3, %4};\n}"
                 ::"r"(smem_u32(a)), "f"(v0), "f"(v1), "f"(v2), "f"(v3), "r"(p) : "memory");
}

__device__ __forceinline__ float warp_sum(float v) {
#pragma unroll
    for (int o = 16; o > 0; o >>= 1) v += __shfl_xor_sync(0xffffffffu, v, o);
    return v;
}
__device__ __forceinline__ float warp_max(float v) {
#pragma unroll
    for (int o = 16; o > 0; o >>= 1) v = fmaxf(v, __shfl_xor_sync(0xffffffffu, v, o));
    return v;
}

constexpr float LOG2E = 1.4426950408889634f;

__device__ __forceinline__ void ln_stats(const float (&v)[18], float pivot, float& mean_b, float& sd_b) {
    float s0 = 0.f, s1 = 0.f, q0 = 0.f, q1 = 0.f;
#pragma unroll
    for (int k = 0; k < 18; k += 2) {
        const float d0 = v[k] - pivot, d1 = v[k + 1] - pivot;
        s0 += d0; s1 += d1; q0 = fmaf(d0, d0, q0); q1 = fmaf(d1, d1, q1);
    }
    float sm = s0 + s1, sq = q0 + q1;
#pragma unroll
    for (int o = 16; o > 0; o >>= 1) {
        sm += __shfl_xor_sync(0xffffffffu, sm, o);
        sq += __shfl_xor_sync(0xffffffffu, sq, o);
    }
    const float dm = sm * (1.0f / DM);
    const float var = fmaxf(fmaf(-dm, dm, sq * (1.0f / DM)), 0.f);
    mean_b = bfr(pivot + dm);
    float sd;
    asm("sqrt.approx.f32 %0, %1;" : "=f"(sd) : "f"(bfr(bfr(var) + 1e-5f)));
    sd_b = bfr(sd);
}
__device__ __forceinline__ float ln_apply(float x, float mean_b, float sd_b) { return bfr(__fdividef(bfr(x - mean_b), sd_b)); }

__device__ __forceinline__ void ldsm4t(uint32_t (&b)[4], uint32_t a) {
    asm volatile("ldmatrix.sync.aligned.m8n8.x4.trans.shared.b16 {%0,%1,%2,%3}, [%4];"
                 : "=r"(b[0]), "=r"(b[1]), "=r"(b[2]), "=r"(b[3]) : "r"(a));
}
__device__ __forceinline__ void mma_row(float (&c)[4], uint32_t alo, uint32_t ahi, uint32_t b0, uint32_t b1) {
    asm("mma.sync.aligned.m16n8k16.row.col.f32.bf16.bf16.f32 {%0,%1,%2,%3}, {%4,%5,%6,%7}, {%8,%9}, {%0,%1,%2,%3};"
        : "+f"(c[0]), "+f"(c[1]), "+f"(c[2]), "+f"(c[3]) : "r"(alo), "r"(0u), "r"(ahi), "r"(0u), "r"(b0), "r"(b1));
}
__device__ __forceinline__ uint32_t pack_bf(float lo, float hi) {
    return (__float_as_uint(lo) >> 16) | (__float_as_uint(hi) & 0xffff0000u);
}

__device__ __forceinline__ float owner_reduce(const unsigned long long* buf, unsigned tag, float* red, int tid, unsigned live) {
    const int warp = tid >> 5, lane = tid & 31;
    const unsigned act = live && tid < 256;
    const unsigned long long* p = buf + (size_t)(tid & 255) * 4;
    unsigned long long a = 0, b = 0, c = 0, d = 0; unsigned n = 0; bool return_from_spin = false;
    while (true) {
        ld_raw2_p(p, a, b, act);
        ld_raw2_p(p + 2, c, d, act);
        if ((pkok(a, tag) && pkok(b, tag) && pkok(c, tag) && pkok(d, tag)) || !act) break;
        if (++n > SPIN_LIMIT) SPIN_FAIL();
        if (return_from_spin) break;
    }
    float v0 = pkv(a), v1 = pkv(b), v2 = pkv(c), v3 = pkv(d);
#pragma unroll
    for (int o = 2; o <= 16; o <<= 1) {
        v0 += __shfl_xor_sync(0xffffffffu, v0, o);
        v1 += __shfl_xor_sync(0xffffffffu, v1, o);
        v2 += __shfl_xor_sync(0xffffffffu, v2, o);
        v3 += __shfl_xor_sync(0xffffffffu, v3, o);
    }
    sts128_p(red + (warp & 7) * 8 + (lane & 1) * 4, v0, v1, v2, v3, act && lane < 2);
    bar_tail_p(live);
    float s0 = 0.f, s1 = 0.f;
#pragma unroll
    for (int w = 0; w < 8; w += 2) { s0 += red[w * 8 + (tid & 7)]; s1 += red[w * 8 + 8 + (tid & 7)]; }
    return s0 + s1;
}

template <int R, int KS>
__device__ __forceinline__ void slab_mma(uint32_t p0, uint32_t p1, uint32_t p2, uint32_t vaddr, unsigned long long* dst,
                                         int warp, int lane, unsigned tag, unsigned live) {
    uint32_t alo[KS], ahi[KS];
#pragma unroll
    for (int ks = 0; ks < KS; ks++) {
        const uint32_t lo = lds32(vaddr + ks * 32 + (lane & 3) * 4), hi = lds32(vaddr + ks * 32 + 16 + (lane & 3) * 4);
        alo[ks] = lane < 4 ? lo : 0u; ahi[ks] = lane < 4 ? hi : 0u;
    }
    auto row_addr = [&](int r) -> uint32_t {
        if (r >= R) r = 0;
        return (r < 12 ? p0 : (r < 24 ? p1 : p2)) + (r % 12) * WP;
    };
    const uint32_t ra = row_addr(lane) + warp * 128, rb = row_addr(32 + (lane & 15)) + warp * 128 + (lane >> 4) * 16;
    uint32_t b[8][4], b2[4][4];
#pragma unroll
    for (int j = 0; j < 8; j++) ldsm4t(b[j], ra + j * 16);
    if (KS == 3) {
#pragma unroll
        for (int j = 0; j < 4; j++) ldsm4t(b2[j], rb + j * 32);
    }
    float c[8][4];
#pragma unroll
    for (int j = 0; j < 8; j++) { c[j][0] = c[j][1] = c[j][2] = c[j][3] = 0.f; mma_row(c[j], alo[0], ahi[0], b[j][0], b[j][1]); }
#pragma unroll
    for (int j = 0; j < 8; j++) mma_row(c[j], alo[1], ahi[1], b[j][2], b[j][3]);
    if (KS == 3) {
#pragma unroll
        for (int j = 0; j < 8; j++) mma_row(c[j], alo[KS - 1], ahi[KS - 1], b2[j >> 1][(j & 1) * 2], b2[j >> 1][(j & 1) * 2 + 1]);
    }
#pragma unroll
    for (int j = 0; j < 8; j++)
        st_pk2_p(dst + (size_t)(warp * 8 + j) * NCTA * 8 + (lane & 3) * 2, c[j][0], c[j][1], tag, live && lane < 4);
}

__device__ __forceinline__ bool gather_chunk(const unsigned long long* base, int qd, int chunk, unsigned tag, float* gp,
                                             int lane, bool block, unsigned live) {
    unsigned long long o[GC], m = 0, l = 0;
    unsigned n = 0; bool return_from_spin = false;
    const unsigned long long* src = base + (size_t)chunk * GC * PREC;
#pragma unroll
    for (int j = 0; j < GC; j++) o[j] = 0;
    unsigned pend = live ? 0xffffffffu : 0u;
    do {
        ld_raw2_p(src + (size_t)lane * PREC + 128, m, l, (pend >> lane) & 1);
#pragma unroll
        for (int j = 0; j < GC; j++)
            asm volatile("{\n.reg .pred q;\nsetp.ne.u32 q, %2, 0;\n@q ld.relaxed.gpu.global.b64 %0, [%1];\n}"
                         : "+l"(o[j]) : "l"(src + (size_t)j * PREC + qd * 32 + lane), "r"((pend >> j) & 1) : "memory");
        unsigned bad = (pkok(m, tag) && pkok(l, tag)) ? 0u : (1u << lane);
#pragma unroll
        for (int j = 0; j < GC; j++) bad |= pkok(o[j], tag) ? 0u : (1u << j);
        pend &= __reduce_or_sync(0xffffffffu, bad);
        if (pend && !block) return false;
        if (++n > SPIN_LIMIT) SPIN_FAIL();
        if (return_from_spin) break;
    } while (pend);
    const float M = warp_max(pkv(m));
    const float e = pkv(m) == -INFINITY ? 0.f : exp2f((pkv(m) - M) * LOG2E);
    const float L = warp_sum(e * pkv(l));
    float O0 = 0.f, O1 = 0.f;
#pragma unroll
    for (int j = 0; j < GC; j += 2) {
        O0 = fmaf(__shfl_sync(0xffffffffu, e, j), pkv(o[j]), O0);
        O1 = fmaf(__shfl_sync(0xffffffffu, e, j + 1), pkv(o[j + 1]), O1);
    }
    sts32_p(gp + chunk * 36 + lane, O0 + O1, live);
    sts64_p(gp + chunk * 36 + 32, M, L, live && lane == 0);
    return true;
}

__global__ void __launch_bounds__(NTHREADS, 1)
fused_decode_kernel(const __nv_bfloat16* __restrict__ x, const __nv_bfloat16* __restrict__ kc,
                    const __nv_bfloat16* __restrict__ vc, const __nv_bfloat16* __restrict__ wq,
                    const __nv_bfloat16* __restrict__ wo, const __nv_bfloat16* __restrict__ wdown,
                    const __grid_constant__ CUtensorMap map_gate, const __grid_constant__ CUtensorMap map_up,
                    __nv_bfloat16* __restrict__ out) {
    extern __shared__ __align__(1024) unsigned char smem[];
    const uint32_t sb = smem_u32(smem);
    const int tid = threadIdx.x, warp = tid >> 5, lane = tid & 31;
    const int cta = blockIdx.x;
    const uint32_t bar_full = sb + SM_BAR, bar_empty = bar_full + S * 8;
    const uint32_t bar_pfull = bar_empty + S * 8, bar_pempty = bar_pfull + PS * 8, bar_q = bar_pempty + PS * 8;
    float* s_pr = reinterpret_cast<float*>(smem + SM_PR);
    float* s_gp = reinterpret_cast<float*>(smem + SM_GP);
    float* s_red = reinterpret_cast<float*>(smem + SM_RED);
    float* s_h = reinterpret_cast<float*>(smem + SM_H);
    float* s_hn = reinterpret_cast<float*>(smem + SM_HN);
    float* s_o = reinterpret_cast<float*>(smem + SM_SMALL);
    float* s_hh = s_o + 9 * 32;
    float* s_hown = s_hh + 40;
    volatile int* s_tid = reinterpret_cast<volatile int*>(s_hown + 8);
    volatile int* s_nkv = s_tid + S;
    volatile int* s_gdone = s_nkv + 1;

    if (warp == 9) {
        const unsigned char* kbase = reinterpret_cast<const unsigned char*>(kc);
        const unsigned char* vbase = reinterpret_cast<const unsigned char*>(vc);
        uint64_t pol = 0;
        unsigned ep = 0;
        if (lane == 0) {
            l2_prefetch(reinterpret_cast<const unsigned char*>(wq) + (size_t)cta * (DM * NH * DH * 2 / NCTA), DM * NH * DH * 2 / NCTA);
#pragma unroll 1
            for (int i = 0; i < 2 * S + 2 * PS + NH; i++) mbar_init(bar_full + i * 8, 1);
            *s_nkv = 0x7fffffff;
            asm volatile("fence.mbarrier_init.release.cluster;" ::: "memory");
            asm volatile("fence.proxy.async.shared::cta;" ::: "memory");
            asm volatile("createpolicy.fractional.L2::evict_first.b64 %0, 1.0;" : "=l"(pol));
#pragma unroll 1
            for (int it = 0; it < DCAP; it++) {
                const int t = it * NCTA + cta;
                s_tid[it] = t;
                mbar_expect_tx(bar_full + it * 8, SLOT_B);
                bulk_load(sb + it * SLOT_B, kbase + (size_t)t * TILE_B, TILE_B, bar_full + it * 8, pol);
                bulk_load(sb + it * SLOT_B + TILE_B, vbase + (size_t)t * TILE_B, TILE_B, bar_full + it * 8, pol);
            }
            ep = *reinterpret_cast<volatile unsigned*>(&g_epoch);
        }
        __syncthreads();
        if (lane == 0) {
            asm volatile("prefetch.tensormap [%0];" ::"l"(&map_gate) : "memory");
            asm volatile("prefetch.tensormap [%0];" ::"l"(&map_up) : "memory");
            unsigned* ctr = &g_ctr[ep & 1][0];
            if (cta == 0) g_ctr[(ep & 1) ^ 1][0] = 0;
            int s = DCAP, sp = 0;
            int use = 0, usep = 0;
            int n = DCAP;
            int tk[LA], tk0[LA];
#pragma unroll
            for (int i = 0; i < LA; i++) { tk[i] = (DCAP + i) * NCTA + cta; tk0[i] = NS * NCTA + (int)atomicAdd(ctr, 1u); }
            auto kv_step = [&](int& t_, int t0_) -> bool {
                const int t = t_;
                if (t >= NTILES) return false;
                if (n + LA < NS) t_ = (n + LA) * NCTA + cta;
                else if (n < NS) t_ = t0_;
                else t_ = NS * NCTA + (int)atomicAdd(ctr, 1u);
                mbar_wait(bar_full + sp * 8, usep & 1);
                if (use > 0) mbar_wait(bar_empty + s * 8, (use - 1) & 1);
                s_tid[s] = t;
                mbar_expect_tx(bar_full + s * 8, SLOT_B);
                bulk_load(sb + s * SLOT_B, kbase + (size_t)t * TILE_B, TILE_B, bar_full + s * 8, pol);
                bulk_load(sb + s * SLOT_B + TILE_B, vbase + (size_t)t * TILE_B, TILE_B, bar_full + s * 8, pol);
                if (++s == S) { s = 0; use++; }
                if (++sp == S) { sp = 0; usep++; }
                n++;
                return true;
            };
            bool more = true;
#pragma unroll 1
            while (more) {
#pragma unroll
                for (int i = 0; i < LA; i++) more = more && kv_step(tk[i], tk0[i]);
            }
            *s_nkv = n;
            {
                int ss = s, su = use;
#pragma unroll 1
                for (int k = 0; k < NW; k++) {
                    mbar_wait(bar_empty + ss * 8, (su - 1) & 1);
                    mbar_arrive(bar_full + ss * 8);
                    if (++ss == S) { ss = 0; su++; }
                }
            }
            const int w0s = s, w0u = use;
#pragma unroll 1
            for (int k = 0; k < NWP; k++) {
                const int pk_ = k - (k < WK1 ? WD1 : DCAPW);
                int sp2 = w0s + pk_, up2 = w0u;
                if (sp2 < 0) { sp2 += S; up2--; } else if (sp2 >= S) { sp2 -= S; up2++; }
                mbar_wait(bar_full + sp2 * 8, (up2 + (pk_ >= 0 && pk_ < NW ? 1 : 0)) & 1);
                mbar_wait(bar_empty + s * 8, (use - 1) & 1);
                const int mat = k / 3, r = k % 3;
                PSTAMP(16 + k);
                if (mat == 0 || mat == 3) {
                    const int rows = (k == 2) ? 8 : 12;
                    const __nv_bfloat16* src = mat == 0 ? wo + ((size_t)cta * 32 + r * 12) * DM : wdown + ((size_t)cta * FC + r * 12) * DM;
                    mbar_expect_tx(bar_full + s * 8, rows * (DM * 2));
#pragma unroll 1
                    for (int i = 0; i < rows; i++) bulk_load(sb + s * SLOT_B + i * WP, src + (size_t)i * DM, DM * 2, bar_full + s * 8, pol);
                } else {
                    mbar_expect_tx(bar_full + s * 8, 192 * FCP * 2);
                    tma_load_2d(sb + s * SLOT_B, mat == 1 ? &map_gate : &map_up, (cta * FC) & ~7, r * 192, bar_full + s * 8);
                }
                if (++s == S) { s = 0; use++; }
            }
        }
        return;
    }

    unsigned short xo;
    STAMP(0);
    unsigned short xr[18], xq[8];
#pragma unroll
    for (int k = 0; k < 18; k++)
        asm volatile("ld.global.nc.u16 %0, [%1];" : "=h"(xr[k]) : "l"(x + lane + 32 * k));
#pragma unroll
    for (int k = 0; k < 8; k++)
        asm volatile("ld.global.nc.u16 %0, [%1];" : "=h"(xq[k]) : "l"(x + (tid >> 2) + 72 * k));
    asm volatile("ld.global.nc.u16 %0, [%1];" : "=h"(xo) : "l"(x + (cta < NOWN ? cta : 0) * 8 + (tid & 7)));
    const unsigned tag = *reinterpret_cast<volatile unsigned*>(&g_epoch) + 1u;
    {
        if (tid < 16) st_pk2(g_q + cta * 32 + tid * 2, 0.f, 0.f, 0u);
        if (tid < 2 * (PREC / 2)) {
            const int hl = tid / (PREC / 2), j = tid % (PREC / 2);
            st_pk2(g_part + ((size_t)(NH - 2 + hl) * NCTA + cta) * PREC + 2 * j, 0.f, 0.f, 0u);
        }
        st_pk2(g_y + ((size_t)(tid >> 2) * NCTA + cta) * 8 + (tid & 3) * 2, 0.f, 0.f, 0u);
        st_pk2(g_z + ((size_t)(tid >> 2) * NCTA + cta) * 8 + (tid & 3) * 2, 0.f, 0.f, 0u);
        if (cta < NOWN && tid < 4) st_pk2(g_h + cta * 8 + tid * 2, 0.f, 0.f, 0u);
    }
    __syncthreads();
    uint4 wv[8];
    {
        const int ch = tid & 3, rg = tid >> 2;
        const uint4* wp = reinterpret_cast<const uint4*>(wq + (size_t)rg * (NH * DH) + cta * 32 + ch * 8);
#pragma unroll
        for (int k = 0; k < 8; k++)
            asm volatile("ld.global.nc.L1::no_allocate.v4.u32 {%0,%1,%2,%3}, [%4];"
                         : "=r"(wv[k].x), "=r"(wv[k].y), "=r"(wv[k].z), "=r"(wv[k].w)
                         : "l"(wp + (size_t)k * 72 * (NH * DH / 8)));
    }
    {
        float xv[18];
#pragma unroll
        for (int k = 0; k < 18; k++) xv[k] = bflo(xr[k]);
        float mean_b, sd_b;
        ln_stats(xv, __shfl_sync(0xffffffffu, xv[0], 0), mean_b, sd_b);
        float xn[8];
#pragma unroll
        for (int k = 0; k < 8; k++) xn[k] = ln_apply(bflo(xq[k]), mean_b, sd_b);
        STAMPD(15, wv[0].x ^ wv[1].x ^ wv[2].x ^ wv[3].x ^ wv[4].x ^ wv[5].x ^ wv[6].x ^ wv[7].x);
        float acc[8];
#pragma unroll
        for (int e = 0; e < 8; e++) acc[e] = 0.f;
#pragma unroll
        for (int k = 0; k < 8; k++) {
            acc[0] = fmaf(xn[k], bflo(wv[k].x), acc[0]); acc[1] = fmaf(xn[k], bfhi(wv[k].x), acc[1]);
            acc[2] = fmaf(xn[k], bflo(wv[k].y), acc[2]); acc[3] = fmaf(xn[k], bfhi(wv[k].y), acc[3]);
            acc[4] = fmaf(xn[k], bflo(wv[k].z), acc[4]); acc[5] = fmaf(xn[k], bfhi(wv[k].z), acc[5]);
            acc[6] = fmaf(xn[k], bflo(wv[k].w), acc[6]); acc[7] = fmaf(xn[k], bfhi(wv[k].w), acc[7]);
        }
        {
            const bool up = lane & 16;
#pragma unroll
            for (int e = 0; e < 4; e++) {
                const float snd = up ? acc[e] : acc[e + 4], kp = up ? acc[e + 4] : acc[e];
                acc[e] = kp + __shfl_xor_sync(0xffffffffu, snd, 16);
            }
        }
        {
            const bool up = lane & 8;
#pragma unroll
            for (int e = 0; e < 2; e++) {
                const float snd = up ? acc[e] : acc[e + 2], kp = up ? acc[e + 2] : acc[e];
                acc[e] = kp + __shfl_xor_sync(0xffffffffu, snd, 8);
            }
        }
        {
            const bool up = lane & 4;
            const float snd = up ? acc[0] : acc[1], kp = up ? acc[1] : acc[0];
            acc[0] = kp + __shfl_xor_sync(0xffffffffu, snd, 4);
        }
        const int col = (lane & 3) * 8 + ((lane >> 4) & 1) * 4 + ((lane >> 3) & 1) * 2 + ((lane >> 2) & 1);
        s_red[warp * 32 + col] = acc[0];
    }
    bar_tail();
    STAMP(11);
    if (tid < 32) {
        float s = 0.f;
#pragma unroll
        for (int w = 0; w < 9; w++) s += s_red[w * 32 + tid];
        st_pk1_p(g_q + cta * 32 + tid, bfr(s), tag, 1u);
    }
    STAMP(1);

    const unsigned long long* gbase = g_part + (size_t)(cta >> 2) * NCTA * PREC;
    {
    unsigned live;
    asm volatile("mov.u32 %0, 1;" : "=r"(live));

    if (warp < NW) {
        const int half = lane >> 4, c = lane & 15;
        const uint32_t loff = half * 256 + c * 16;
        int slot = warp, use = 0;
#pragma unroll 1
        for (int it = warp;; it += NW) {
            int head = -1;
            {
                unsigned n = 0; bool return_from_spin = false;
                while (it < *s_nkv) {
                    if (mbar_try(bar_full + slot * 8, use & 1)) { if (it < *s_nkv) head = s_tid[slot] >> 9; break; }
                    if (++n > SPIN_LIMIT) SPIN_FAIL();
                    if (return_from_spin) break;
                }
            }
            const int ps = it % PS;
            float* pp = s_pr + ps * PREC;
            if (head < 0) {
                if (it == *s_nkv) {
                    if (it >= PS) mbar_wait(bar_pempty + ps * 8, ((it / PS) - 1) & 1);
                    if (lane == 0) { reinterpret_cast<int*>(pp)[130] = -1; mbar_arrive(bar_pfull + ps * 8); }
                }
                break;
            }
            mbar_wait(bar_q + head * 8, 0);
            float qf[8];
            {
                const uint4 qq = lds128(sb + SM_Q + head * (DH * 2) + c * 16);
                qf[0] = bflo(qq.x); qf[1] = bfhi(qq.x); qf[2] = bflo(qq.y); qf[3] = bfhi(qq.y);
                qf[4] = bflo(qq.z); qf[5] = bfhi(qq.z); qf[6] = bflo(qq.w); qf[7] = bfhi(qq.w);
            }
            const uint32_t kaddr = sb + slot * SLOT_B + loff;
            float s[16];
#pragma unroll
            for (int j = 0; j < 16; j++) {
                const uint4 kv = lds128(kaddr + j * 512);
                float d0 = qf[0] * bflo(kv.x), d1 = qf[1] * bfhi(kv.x);
                d0 = fmaf(qf[2], bflo(kv.y), d0); d1 = fmaf(qf[3], bfhi(kv.y), d1);
                d0 = fmaf(qf[4], bflo(kv.z), d0); d1 = fmaf(qf[5], bfhi(kv.z), d1);
                d0 = fmaf(qf[6], bflo(kv.w), d0); d1 = fmaf(qf[7], bfhi(kv.w), d1);
                s[j] = d0 + d1;
            }
            {
                const bool up = c & 8;
#pragma unroll
                for (int j = 0; j < 8; j++) {
                    const float snd = up ? s[j] : s[j + 8], kp = up ? s[j + 8] : s[j];
                    s[j] = kp + __shfl_xor_sync(0xffffffffu, snd, 8);
                }
            }
            {
                const bool up = c & 4;
#pragma unroll
                for (int j = 0; j < 4; j++) {
                    const float snd = up ? s[j] : s[j + 4], kp = up ? s[j + 4] : s[j];
                    s[j] = kp + __shfl_xor_sync(0xffffffffu, snd, 4);
                }
            }
            {
                const bool up = c & 2;
#pragma unroll
                for (int j = 0; j < 2; j++) {
                    const float snd = up ? s[j] : s[j + 2], kp = up ? s[j + 2] : s[j];
                    s[j] = kp + __shfl_xor_sync(0xffffffffu, snd, 2);
                }
            }
            {
                const bool up = c & 1;
                const float snd = up ? s[0] : s[1], kp = up ? s[1] : s[0];
                s[0] = kp + __shfl_xor_sync(0xffffffffu, snd, 1);
            }
            const float sc = bfr(bfr(s[0]) * 0.08838834764831845f);
            const float m = warp_max(sc);
            const float p = exp2f((sc - m) * LOG2E);
            float acc[8];
#pragma unroll
            for (int e = 0; e < 8; e++) acc[e] = 0.f;
            const uint32_t vaddr = kaddr + TILE_B;
#pragma unroll
            for (int j = 0; j < 16; j++) {
                const uint4 vv = lds128(vaddr + j * 512);
                const float pj = __shfl_sync(0xffffffffu, p, (lane & 16) + j);
                acc[0] = fmaf(pj, bflo(vv.x), acc[0]); acc[1] = fmaf(pj, bfhi(vv.x), acc[1]);
                acc[2] = fmaf(pj, bflo(vv.y), acc[2]); acc[3] = fmaf(pj, bfhi(vv.y), acc[3]);
                acc[4] = fmaf(pj, bflo(vv.z), acc[4]); acc[5] = fmaf(pj, bfhi(vv.z), acc[5]);
                acc[6] = fmaf(pj, bflo(vv.w), acc[6]); acc[7] = fmaf(pj, bfhi(vv.w), acc[7]);
            }
            __syncwarp();
            if (lane == 0) mbar_arrive(bar_empty + slot * 8);
            slot += NW; if (slot >= S) { slot -= S; use++; }
            float r4[4];
#pragma unroll
            for (int e = 0; e < 4; e++) {
                const float snd = half ? acc[e] : acc[e + 4], kp = half ? acc[e + 4] : acc[e];
                r4[e] = kp + __shfl_xor_sync(0xffffffffu, snd, 16);
            }
            const float l = warp_sum(p);
            if (it >= PS) mbar_wait(bar_pempty + ps * 8, ((it / PS) - 1) & 1);
            *reinterpret_cast<float4*>(pp + c * 8 + half * 4) = make_float4(r4[0], r4[1], r4[2], r4[3]);
            if (lane == 0) *reinterpret_cast<float4*>(pp + 128) = make_float4(m, l, __int_as_float(head), 0.f);
            __syncwarp();
            if (lane == 0) mbar_arrive(bar_pfull + ps * 8);
        }
    } else if (live && warp == 8) {
        int qn = 0;
        auto fetch_q = [&]() {
            const unsigned long long* src = g_q + qn * DH + lane * 4;
            unsigned long long a[8], b[8]; unsigned n = 0; bool return_from_spin = false;
            while (true) {
                bool ok = true;
#pragma unroll
                for (int j = 0; j < 4; j++) { ld_raw2(src + j * DH, a[2 * j], b[2 * j]); ld_raw2(src + j * DH + 2, a[2 * j + 1], b[2 * j + 1]); }
#pragma unroll
                for (int j = 0; j < 8; j++) ok = ok && pkok(a[j], tag) && pkok(b[j], tag);
                if (ok) break;
                if (++n > SPIN_LIMIT) SPIN_FAIL();
                if (return_from_spin) break;
            }
#pragma unroll
            for (int j = 0; j < 4; j++)
                *reinterpret_cast<uint2*>(smem + SM_Q + (qn + j) * (DH * 2) + lane * 8) =
                    make_uint2(((unsigned)a[2 * j] >> 16) | ((unsigned)b[2 * j] & 0xffff0000u),
                               ((unsigned)a[2 * j + 1] >> 16) | ((unsigned)b[2 * j + 1] & 0xffff0000u));
            __syncwarp();
            if (lane < 4) mbar_arrive(bar_q + (qn + lane) * 8);
            qn += 4;
        };
        fetch_q();
        int gdone = 0;
        int cur = 0;
        float M = -INFINITY, L = 0.f, a0 = 0.f, a1 = 0.f, a2 = 0.f, a3 = 0.f;
#pragma unroll 1
        for (int it = 0;; it++) {
            const int ps = it % PS;
            while (qn < NH && (qn < cur + 4 || !mbar_test(bar_pfull + ps * 8, (it / PS) & 1))) fetch_q();
            if (cur > (cta >> 2) + 1) {
                while (gdone < NGC && !mbar_test(bar_pfull + ps * 8, (it / PS) & 1)) {
                    if (!gather_chunk(gbase, cta & 3, gdone, tag, s_gp, lane, false, 1u)) break;
                    gdone++;
                }
            }
            mbar_wait(bar_pfull + ps * 8, (it / PS) & 1);
            const float* pp = s_pr + ps * PREC;
            const float4 v = *reinterpret_cast<const float4*>(pp + lane * 4);
            const float4 ml = *reinterpret_cast<const float4*>(pp + 128);
            __syncwarp();
            if (lane == 0) mbar_arrive(bar_pempty + ps * 8);
            int head = __float_as_int(ml.z);
            if (head < 0) head = NH;
#pragma unroll 1
            for (; cur < head; cur++) {
                unsigned long long* dst = g_part + ((size_t)cur * NCTA + cta) * PREC;
                st_pk2(dst + lane * 4, a0, a1, tag);
                st_pk2(dst + lane * 4 + 2, a2, a3, tag);
                if (lane == 0) st_pk2(dst + 128, M, L, tag);
                M = -INFINITY; L = 0.f; a0 = a1 = a2 = a3 = 0.f;
            }
            if (head == NH) break;
            const float Mn = fmaxf(M, ml.x);
            const float ea = exp2f((M - Mn) * LOG2E), eb = exp2f((ml.x - Mn) * LOG2E);
            M = Mn;
            L = L * ea + ml.y * eb;
            a0 = a0 * ea + v.x * eb; a1 = a1 * ea + v.y * eb; a2 = a2 * ea + v.z * eb; a3 = a3 * ea + v.w * eb;
        }
        if (lane == 0) *s_gdone = gdone;
    }
    bar_tail_p(live);
    STAMP(2);
    const int nkv = live ? *s_nkv : 0;
    const int w0s = nkv % S, w0u = nkv / S;
    auto piece = [&](int k) -> uint32_t { int ps = w0s + k; if (ps >= S) ps -= S; return sb + ps * SLOT_B; };
    auto piece_wait = [&](int k0, int cnt) {
        const int k = k0 + (lane < cnt ? lane : 0);
        int ps = w0s + k, pu = w0u; if (ps >= S) { ps -= S; pu++; }
        mbar_wait_p(bar_full + ps * 8, (pu + (k < NW ? 1 : 0)) & 1, live);
    };
    if (warp == 8) piece_wait(0, 3);
#pragma unroll 1
    for (int ch = (live ? *s_gdone : 0) + (live ? warp : 0); ch < (live ? NGC : 1); ch += 9)
        gather_chunk(gbase, cta & 3, ch, tag, s_gp, lane, true, live);
    bar_tail_p(live);
    STAMP(3);
    {
        float M = s_gp[32];
#pragma unroll
        for (int j = 1; j < NGC; j++) M = fmaxf(M, s_gp[j * 36 + 32]);
        float o0 = 0.f, o1 = 0.f, L = 0.f;
#pragma unroll
        for (int j = 0; j < NGC; j++) {
            const float2 ml = *reinterpret_cast<const float2*>(s_gp + j * 36 + 32);
            const float e = ml.x == -INFINITY ? 0.f : exp2f((ml.x - M) * LOG2E);
            L = fmaf(e, ml.y, L);
            if (j & 1) o1 = fmaf(e, s_gp[j * 36 + lane], o1); else o0 = fmaf(e, s_gp[j * 36 + lane], o0);
        }
        const float o = bfr(__fdividef(o0 + o1, L));
        const float on = __shfl_down_sync(0xffffffffu, o, 1);
        sts32_p(s_o + warp * 32 + (lane >> 1), __uint_as_float(pack_bf(o, on)), live && !(lane & 1));
        __syncwarp();
    }
    STAMP(12);
    slab_mma<32, 2>(piece(0), piece(1), piece(2), smem_u32(s_o + warp * 32), g_y + (size_t)cta * 8, warp, lane, tag, live);
    STAMP(4);
    if (cta < NOWN) {
        const float s = owner_reduce(g_y + (size_t)cta * NCTA * 8, tag, s_red, tid, live);
        const float h = bfr(bflo(xo) + bfr(s));
        st_pk1_p(g_h + cta * 8 + (tid & 7), h, tag, live && tid < 8);
        sts32_p(s_hown + (tid & 7), h, live && tid < 8);
    }
    STAMP(5);
    if (warp == 8) piece_wait(3, 6);
    {
        const float2 v = ld_pk2_p(g_h + 2 * tid, tag, live);
        sts64_p(s_h + 2 * tid, v.x, v.y, live);
        bar_tail_p(live);
    }
    STAMP(6);
    {
        float hv[18];
#pragma unroll
        for (int k = 0; k < 18; k++) hv[k] = s_h[lane + 32 * k];
        float mean_b, sd_b;
        ln_stats(hv, __shfl_sync(0xffffffffu, hv[0], 0), mean_b, sd_b);
        const float2 hh2 = *reinterpret_cast<const float2*>(s_h + 2 * tid);
        const float n0 = ln_apply(hh2.x, mean_b, sd_b), n1 = ln_apply(hh2.y, mean_b, sd_b);
        sts32_p(s_hn + tid, __uint_as_float(pack_bf(n0, n1)), live);
    }
    bar_tail_p(live);
    STAMP(7);
    {
        uint32_t af[4][2];
#pragma unroll
        for (int ks = 0; ks < 4; ks++) {
            const uint32_t a = sb + SM_HN + (warp * 64 + ks * 16 + (lane & 3) * 2) * 2;
            const uint32_t lo = lds32(a), hi = lds32(a + 16);
            af[ks][0] = lane < 4 ? lo : 0u; af[ks][1] = lane < 4 ? hi : 0u;
        }
        const uint32_t roff = ((warp % 3) * 64 + lane) * (FCP * 2);
        uint32_t b[2][5][2][4];
#pragma unroll
        for (int mat = 0; mat < 2; mat++) {
            const uint32_t base = piece(3 + mat * 3 + warp / 3) + roff;
#pragma unroll
            for (int nt = 0; nt < 5; nt++) {
                ldsm4t(b[mat][nt][0], base + nt * 16);
                ldsm4t(b[mat][nt][1], base + 32 * (FCP * 2) + nt * 16);
            }
        }
        float c[2][5][4];
#pragma unroll
        for (int ks = 0; ks < 4; ks++)
#pragma unroll
            for (int mat = 0; mat < 2; mat++)
#pragma unroll
                for (int nt = 0; nt < 5; nt++) {
                    if (ks == 0) c[mat][nt][0] = c[mat][nt][1] = c[mat][nt][2] = c[mat][nt][3] = 0.f;
                    mma_row(c[mat][nt], af[ks][0], af[ks][1], b[mat][nt][ks >> 1][(ks & 1) * 2], b[mat][nt][ks >> 1][(ks & 1) * 2 + 1]);
                }
#pragma unroll
        for (int mat = 0; mat < 2; mat++)
#pragma unroll
            for (int nt = 0; nt < 5; nt++)
                sts64_p(s_red + warp * 80 + mat * 40 + nt * 8 + (lane & 3) * 2, c[mat][nt][0], c[mat][nt][1], live && lane < 4);
    }
    bar_tail_p(live);
    if (warp == 8) piece_wait(9, 3);
    if (tid < 64 || !live) {
        const int col = (live ? tid : lane) < FC ? (live ? tid : lane) : 0;
        const float* pr = s_red + col + (cta & 1) * 4;
        float g0 = pr[0], g1 = 0.f, u0 = pr[40], u1 = 0.f;
#pragma unroll
        for (int w = 1; w < 9; w += 2) {
            g1 += pr[w * 80]; u1 += pr[w * 80 + 40];
            g0 += pr[w * 80 + 80]; u0 += pr[w * 80 + 120];
        }
        const float g = bfr(g0 + g1), u = bfr(u0 + u1);
        const float inner = 0.7978845608028654f * (g + 0.044715f * g * g * g);
        const float ge = bfr(0.5f * g * (1.0f + tanhf(inner)));
        const float hh = tid < FC ? bfr(ge * u) : 0.f;
        const float hn2 = __shfl_down_sync(0xffffffffu, hh, 1);
        sts32_p(s_hh + (tid >> 1), __uint_as_float(pack_bf(hh, hn2)), live && !(tid & 1) && tid < 48);
    }
    bar_tail_p(live);
    STAMP(8);
    slab_mma<FC, 3>(piece(9), piece(10), piece(11), smem_u32(s_hh), g_z + (size_t)cta * 8, warp, lane, tag, live);
    STAMP(9);
    if (cta < NOWN) {
        const float s = owner_reduce(g_z + (size_t)cta * NCTA * 8, tag, s_red, tid, live);
        const unsigned short r = __bfloat16_as_ushort(__float2bfloat16_rn(s_hown[tid & 7] + bfr(s)));
        asm volatile("{\n.reg .pred q;\nsetp.ne.u32 q, %2, 0;\n@q st.global.u16 [%0], %1;\n}"
                     ::"l"(out + cta * 8 + (tid & 7)), "h"(r), "r"((unsigned)(live && tid < 8)) : "memory");
        asm volatile("{\n.reg .pred q;\nsetp.ne.u32 q, %2, 0;\n@q st.relaxed.gpu.global.u32 [%0], %1;\n}"
                     ::"l"(&g_epoch), "r"(tag), "r"((unsigned)(live && cta == 0 && tid == 0)) : "memory");
    }
    STAMP(10);
    }
}

typedef CUresult (*PFN_encodeTiled)(CUtensorMap*, CUtensorMapDataType, cuuint32_t, void*, const cuuint64_t*,
                                    const cuuint64_t*, const cuuint32_t*, const cuuint32_t*, CUtensorMapInterleave,
                                    CUtensorMapSwizzle, CUtensorMapL2promotion, CUtensorMapFloatOOBfill);

void make_map(PFN_encodeTiled enc, CUtensorMap* m, const void* ptr) {
    cuuint64_t dims[2] = {(cuuint64_t)DFF, (cuuint64_t)DM};
    cuuint64_t strides[1] = {(cuuint64_t)DFF * 2};
    cuuint32_t box[2] = {(cuuint32_t)FCP, 192u};
    cuuint32_t estr[2] = {1u, 1u};
    enc(m, CU_TENSOR_MAP_DATA_TYPE_BFLOAT16, 2, const_cast<void*>(ptr), dims, strides, box, estr,
        CU_TENSOR_MAP_INTERLEAVE_NONE, CU_TENSOR_MAP_SWIZZLE_NONE, CU_TENSOR_MAP_L2_PROMOTION_L2_128B,
        CU_TENSOR_MAP_FLOAT_OOB_FILL_NONE);
}

}

extern "C" void kernel_launch(void* const* d_in, const int* in_sizes, int n_in, void* d_out, int out_size) {
    (void)in_sizes; (void)n_in; (void)out_size;
    static PFN_encodeTiled enc = nullptr;
    if (!enc) {
        void* fn = nullptr;
        cudaDriverEntryPointQueryResult st;
        cudaGetDriverEntryPoint("cuTensorMapEncodeTiled", &fn, cudaEnableDefault, &st);
        enc = reinterpret_cast<PFN_encodeTiled>(fn);
        cudaFuncSetAttribute(fused_decode_kernel, cudaFuncAttributeMaxDynamicSharedMemorySize, SM_TOTAL);
    }
    CUtensorMap mg, mu;
    make_map(enc, &mg, d_in[6]);
    make_map(enc, &mu, d_in[7]);
    fused_decode_kernel<<<NCTA, NTHREADS, SM_TOTAL>>>(
        (const __nv_bfloat16*)d_in[0], (const __nv_bfloat16*)d_in[1], (const __nv_bfloat16*)d_in[2],
        (const __nv_bfloat16*)d_in[3], (const __nv_bfloat16*)d_in[4], (const __nv_bfloat16*)d_in[8], mg, mu,
        (__nv_bfloat16*)d_out);
}
```
